```python
import torch

def _softmax(x, axis=-1):
    return torch.softmax(x, dim=axis)
def _gelu(x):
    return torch.nn.functional.gelu(x, approximate="tanh")
def _silu(x):
    return torch.nn.functional.silu(x)
def _sigmoid(x):
    return torch.sigmoid(x)
def _layernorm(x, axis=-1, eps=1e-5):
    m = x.mean(dim=axis, keepdim=True)
    v = x.var(dim=axis, keepdim=True, unbiased=False)
    return (x - m) / torch.sqrt(v + eps)
def _scatter_add(tgt, idx, src, axis=0):
    return tgt.clone().index_add_(axis, idx, src)
def _segment_sum(src, seg, n):
    out = torch.zeros((n,) + src.shape[1:], dtype=src.dtype)
    return out.index_add_(0, seg, src)
def _pad(x, pw):
    flat = tuple(v for pair in reversed(pw) for v in pair)
    return torch.nn.functional.pad(x, flat)

kernel_name = 'sequential_preLN__sliding_block_cached__dense_activation_relu__decode'

def setup_inputs():

    _w = (lambda a: (lambda t: t.to(torch.bfloat16) if t.is_floating_point() else t)(torch.as_tensor(a)))
    def _A_setup():
        B, Sq, D = 1, 1, 640
        Hq, Hkv, Sk, Dh = 32, 32, 4096, 128
        assert Hq % Hkv == 0, (Hq, Hkv)
        return {
            "x": _w((lambda *s: torch.randn(*s, dtype=torch.bfloat16) * 0.05)(B, Sq, D)),
            "k_cache": _w((lambda *s: torch.randn(*s, dtype=torch.bfloat16) * 3.2)(B, Hkv, Sk, Dh)),
            "v_cache": _w((lambda *s: torch.randn(*s, dtype=torch.bfloat16) * 0.4)(B, Hkv, Sk, Dh)),
            "wq": _w((lambda *s: torch.randn(*s, dtype=torch.bfloat16) * 3.2)(D, Hq * Dh) * (D ** -0.5)),
            "wo": _w((lambda *s: torch.randn(*s, dtype=torch.bfloat16) * 0.4)(Hq * Dh, D) * ((Hq * Dh) ** -0.5)),
        }
    _A_in = _A_setup()

    def _B_setup():
        B, S, D, Dff = 1, 1, 640, 1728
        return {
            "x": _w((lambda *s: torch.randn(*s, dtype=torch.bfloat16) * 0.05)(B, S, D)),
            "w1": _w((lambda *s: torch.randn(*s, dtype=torch.bfloat16) * 0.05)(D, Dff)),
            "w2": _w((lambda *s: torch.randn(*s, dtype=torch.bfloat16) * 0.05)(Dff, D)),
        }
    _B_in = _B_setup()

    return {
        "A_x": _A_in["x"],
        "A_k_cache": _A_in["k_cache"],
        "A_v_cache": _A_in["v_cache"],
        "A_wq": _A_in["wq"],
        "A_wo": _A_in["wo"],
        "B_x": _B_in["x"],
        "B_w1": _B_in["w1"],
        "B_w2": _B_in["w2"],
    }

def reference(A_x, A_k_cache, A_v_cache, A_wq, A_wo, B_x, B_w1, B_w2):
    def _A_ref(x, k_cache, v_cache, wq, wo):
        B, Sq, D = x.shape
        Hq, Dh = 32, 128
        Hkv, Sk = k_cache.shape[1], k_cache.shape[2]
        W = min(4096, max(256, Sk // 4))
        rep = Hq // Hkv
        q = (lambda x, *d: x.permute(*d))((x @ wq).reshape(B, Sq, Hq, Dh), 0, 2, 1, 3)
        k = (lambda x, n, axis: torch.repeat_interleave(x, n, dim=axis))(k_cache[:, :, Sk - W:, :], rep, axis=1)
        v = (lambda x, n, axis: torch.repeat_interleave(x, n, dim=axis))(v_cache[:, :, Sk - W:, :], rep, axis=1)
        scores = torch.einsum("bhqd,bhkd->bhqk", q, k) * (Dh ** -0.5)
        p = _softmax(scores, axis=-1)
        o = torch.einsum("bhqk,bhkd->bhqd", p, v)
        return (lambda x, *d: x.permute(*d))(o, 0, 2, 1, 3).reshape(B, Sq, Hq * Dh) @ wo

    def _B_ref(x, w1, w2):
        h = torch.einsum("bsd,df->bsf", x, w1)
        zero = torch.zeros_like(h)
        h = torch.maximum(h, zero)
        return torch.einsum("bsf,fd->bsd", h, w2)

    x = A_x
    h = x + _A_ref(_layernorm(x, axis=-1), A_k_cache, A_v_cache, A_wq, A_wo)
    h2 = h + _B_ref(_layernorm(h, axis=-1), B_w1, B_w2)
    return h2
```

```cpp
#include <cuda_runtime.h>
#include <cuda_bf16.h>
#include <cuda.h>
#include <stdint.h>

namespace {

constexpr int D = 640, DH = 128, NH = 32, SK = 4096, WIN = 1024, DFF = 1728;
constexpr int NCTA = 128;
constexpr int NO = 80;
constexpr int F1_FIRST = 34;
constexpr int F2_FIRST = 88;
constexpr int NTHREADS = 608;

#define PF_T0 1300.0f
#define PF_PACE 164.0f
#define LD_T0 1800.0f
#define LD_PACE 164.0f
#define PROBE_T 2500.f
#define SC_DELAY 300
#define SC_BACKOFF 100
#define O_DELAY 300
#define O_BACKOFF 0
#define H_BACKOFF 0
#define F_BACKOFF 0

constexpr int FIN_PITCH = 28;
constexpr int SM_K = 0;
constexpr int SM_V = 65536;
constexpr int SM_WO = 131072;
constexpr int SM_RED = SM_WO + 65536;
constexpr int SM_PART2 = SM_RED + 32 * 36 * 4;
constexpr int SM_FIN = SM_PART2 + 32 * 36 * 4;
constexpr int SM_ST = SM_FIN + 32 * FIN_PITCH * 4;
constexpr int SM_QS = SM_ST + 96;
constexpr int SM_X = SM_QS + 256;
constexpr int SM_XN = SM_X + 1280;
constexpr int SM_MW = SM_XN + 1280;
constexpr int SM_LW = SM_MW + 64;
constexpr int SM_BAR = SM_LW + 64;
constexpr int SM_EP = SM_BAR + 224;
constexpr int SM_TOTAL = SM_EP + 32;

constexpr int B_K = 0, B_V = 4, B_WO = 12, B_W1 = 20, B_KFREE = 25, NBAR = 26;
constexpr float U_WO = 1.25f, U_W1 = 0.84375f, U_W2 = 0.625f;
constexpr int SPIN_MAX = 1 << 20;
constexpr unsigned FULL = 0xffffffffu;
constexpr float LOG2E = 1.4426950408889634f;

constexpr int A_QX = 16384;
constexpr int A_SX = A_QX + NCTA * 128;
constexpr int A_EP = A_SX + NH * WIN;
constexpr int A_WORDS = A_EP + 32;
__device__ uint32_t g_arena[A_WORDS + 16384];
__device__ __forceinline__ int a_o(int s, int i) { return (i >> 10) * 4096 + s * 1024 + (i & 1023); }
__device__ __forceinline__ int a_hp(int s, int k, int i) { return k * 4096 + (3 - s) * 1024 + i; }
__device__ __forceinline__ int a_h1(int s, int tile, int i) { return (tile >> 2) * 4096 + (3 - s) * 1024 + D + (tile & 3) * 64 + i; }
#define TL(slot) do {} while (0)
#define TLD(slot, dep) do {} while (0)

__device__ __forceinline__ uint32_t gtime() { uint32_t t; asm volatile("mov.u32 %0, %%globaltimer_lo;" : "=r"(t) :: "memory"); return t; }
__device__ __forceinline__ uint32_t clk32() { uint32_t t; asm volatile("mov.u32 %0, %%clock;" : "=r"(t) :: "memory"); return t; }
__device__ __forceinline__ uint32_t pack2(float lo, float hi) { uint32_t d; asm("cvt.rn.bf16x2.f32 %0, %1, %2;" : "=r"(d) : "f"(hi), "f"(lo)); return d; }
__device__ __forceinline__ float bfr(float x) { return __uint_as_float(pack2(0.f, x)); }
__device__ __forceinline__ float bf_lo(uint32_t w) { return __uint_as_float(w << 16); }
__device__ __forceinline__ float bf_hi(uint32_t w) { return __uint_as_float(w & 0xffff0000u); }
__device__ __forceinline__ uint32_t tagw(float v, uint32_t tag) { return (__float_as_uint(v) & 0xffffff00u) | tag; }
__device__ __forceinline__ float untag(uint32_t w) { return __uint_as_float(w & 0xffffff00u); }
__device__ __forceinline__ uint32_t bad4(const uint4& v, uint32_t tag) { return ((v.x ^ tag) | (v.y ^ tag) | (v.z ^ tag) | (v.w ^ tag)) & 0xffu; }
__device__ __forceinline__ int perm16(int i) { return (i & ~15) | ((i & 6) << 1) | ((i & 8) >> 2) | (i & 1); }

__device__ __forceinline__ void mbar_init(uint32_t bar, uint32_t cnt) { asm volatile("mbarrier.init.shared::cta.b64 [%0], %1;" :: "r"(bar), "r"(cnt) : "memory"); }
__device__ __forceinline__ void mbar_expect_tx(uint32_t bar, uint32_t bytes) { asm volatile("mbarrier.arrive.expect_tx.shared::cta.b64 _, [%0], %1;" :: "r"(bar), "r"(bytes) : "memory"); }
__device__ __forceinline__ void mbar_arrive(uint32_t bar) { asm volatile("mbarrier.arrive.shared::cta.b64 _, [%0];" :: "r"(bar) : "memory"); }
__device__ __forceinline__ void mbar_wait(uint32_t bar) {
    uint32_t done; int it = 0;
    do {
        asm volatile("{\n.reg .pred p;\nmbarrier.try_wait.parity.shared::cta.b64 p, [%1], 0, 20000;\nselp.u32 %0, 1, 0, p;\n}" : "=r"(done) : "r"(bar) : "memory");
    } while (!done && ++it < SPIN_MAX);
}
__device__ __forceinline__ bool mbar_test(uint32_t bar) {
    uint32_t done;
    asm volatile("{\n.reg .pred p;\nmbarrier.test_wait.parity.shared::cta.b64 p, [%1], 0;\nselp.u32 %0, 1, 0, p;\n}" : "=r"(done) : "r"(bar) : "memory");
    return __all_sync(0xffffffffu, done);
}
__device__ __forceinline__ uint64_t policy_evict_first() { uint64_t p; asm volatile("createpolicy.fractional.L2::evict_first.b64 %0, 1.0;" : "=l"(p)); return p; }
__device__ __forceinline__ void bulk_g2s(uint32_t dst, const void* src, uint32_t bytes, uint32_t bar, uint64_t pol) {
    asm volatile("cp.async.bulk.shared::cluster.global.mbarrier::complete_tx::bytes.L2::cache_hint [%0], [%1], %2, [%3], %4;" :: "r"(dst), "l"(src), "r"(bytes), "r"(bar), "l"(pol) : "memory");
}
__device__ __forceinline__ void tma2d(uint32_t dst, const CUtensorMap* m, int c0, int c1, uint32_t bar, uint64_t pol) {
    asm volatile("cp.async.bulk.tensor.2d.shared::cluster.global.mbarrier::complete_tx::bytes.L2::cache_hint [%0], [%1, {%3, %4}], [%2], %5;" :: "r"(dst), "l"(m), "r"(bar), "r"(c0), "r"(c1), "l"(pol) : "memory");
}
__device__ __forceinline__ void prefetch_l2(const void* src, uint32_t bytes) {
    asm volatile("cp.async.bulk.prefetch.L2.global [%0], %1;" :: "l"(src), "r"(bytes) : "memory");
}
__device__ __forceinline__ void wait_until(uint32_t t0, float tns) {
    const uint32_t tgt = t0 + (uint32_t)(int)tns; int it = 0;
    while ((int)(gtime() - tgt) < 0 && ++it < SPIN_MAX) {}
}
__device__ __forceinline__ void bar_sync(int id, int n) { asm volatile("bar.sync %0, %1;" :: "r"(id), "r"(n) : "memory"); }
__device__ __forceinline__ void bar_arrive(int id, int n) { asm volatile("bar.arrive %0, %1;" :: "r"(id), "r"(n) : "memory"); }
__device__ __forceinline__ uint4 ldg_stream(const void* p, uint64_t pol) {
    uint4 v; asm volatile("ld.global.nc.L1::no_allocate.L2::cache_hint.v4.u32 {%0,%1,%2,%3}, [%4], %5;" : "=r"(v.x), "=r"(v.y), "=r"(v.z), "=r"(v.w) : "l"(p), "l"(pol)); return v;
}
__device__ __forceinline__ uint4 ld_rlx4(const void* p) {
    uint4 v; asm volatile("ld.relaxed.gpu.global.v4.u32 {%0,%1,%2,%3}, [%4];" : "=r"(v.x), "=r"(v.y), "=r"(v.z), "=r"(v.w) : "l"(p) : "memory"); return v;
}
__device__ __forceinline__ uint2 ld_rlx2(const void* p) {
    uint2 v; asm volatile("ld.relaxed.gpu.global.v2.u32 {%0,%1}, [%2];" : "=r"(v.x), "=r"(v.y) : "l"(p) : "memory"); return v;
}
__device__ __forceinline__ uint32_t ld_rlx1(const void* p) {
    uint32_t v; asm volatile("ld.relaxed.gpu.global.u32 %0, [%1];" : "=r"(v) : "l"(p) : "memory"); return v;
}
__device__ __forceinline__ void st_rlx1(void* p, uint32_t v) { asm volatile("st.relaxed.gpu.global.u32 [%0], %1;" :: "l"(p), "r"(v) : "memory"); }
__device__ __forceinline__ float sqrt_apx(float x) { float y; asm("sqrt.approx.f32 %0, %1;" : "=f"(y) : "f"(x)); return y; }
__device__ __forceinline__ float ex2(float x) { float y; asm("ex2.approx.ftz.f32 %0, %1;" : "=f"(y) : "f"(x)); return y; }
__device__ __forceinline__ float rcp_apx(float x) { float y; asm("rcp.approx.ftz.f32 %0, %1;" : "=f"(y) : "f"(x)); return y; }
__device__ __forceinline__ float shx(float v, int m) { return __shfl_xor_sync(FULL, v, m); }
__device__ __forceinline__ void delay(uint32_t n) { uint32_t t0 = clk32(); while (clk32() - t0 < n) {} }
__device__ __forceinline__ float sum4(const float4& a) { return (a.x + a.y) + (a.z + a.w); }

__device__ __forceinline__ void mma(float* d, uint32_t a0, uint32_t a1, uint32_t a2, uint32_t a3, uint32_t b0, uint32_t b1) {
    asm("mma.sync.aligned.m16n8k16.row.col.f32.bf16.bf16.f32 {%0,%1,%2,%3}, {%4,%5,%6,%7}, {%8,%9}, {%0,%1,%2,%3};"
        : "+f"(d[0]), "+f"(d[1]), "+f"(d[2]), "+f"(d[3]) : "r"(a0), "r"(a1), "r"(a2), "r"(a3), "r"(b0), "r"(b1));
}
__device__ __forceinline__ void ldsm4t(uint32_t* r, uint32_t addr) {
    asm volatile("ldmatrix.sync.aligned.m8n8.x4.trans.shared.b16 {%0,%1,%2,%3}, [%4];" : "=r"(r[0]), "=r"(r[1]), "=r"(r[2]), "=r"(r[3]) : "r"(addr) : "memory");
}
template <int NV, int STRIDE, int BACKOFF>
__device__ __forceinline__ void poll4(uint4* v, const uint32_t* p, uint32_t tag) {
#pragma unroll
    for (int i = 0; i < NV; i++) v[i] = ld_rlx4(p + i * STRIDE);
#pragma unroll 1
    for (int it = 0; it < SPIN_MAX; it++) {
        uint32_t bad = 0;
#pragma unroll
        for (int i = 0; i < NV; i++) bad |= bad4(v[i], tag) ? (1u << i) : 0u;
        bad = __reduce_or_sync(FULL, bad);
        if (!bad) break;
        if (BACKOFF) delay(BACKOFF);
#pragma unroll
        for (int i = 0; i < NV; i++) if (bad & (1u << i)) v[i] = ld_rlx4(p + i * STRIDE);
    }
}
__device__ __forceinline__ void frags(uint32_t (*af)[4], uint32_t tile, int lane) {
    const uint32_t ad = tile + ((lane & 7) + 8 * (lane >> 4)) * 64 + ((((lane >> 3) & 1) ^ ((lane >> 1) & 3)) << 4);
#pragma unroll
    for (int j = 0; j < 8; j++) ldsm4t(af[j], (ad ^ ((j >> 2) << 5)) + (j & 3) * 1024);
}
__device__ __forceinline__ void mma8(float (*e)[4], const uint32_t (*af)[4], uint32_t b0, uint32_t b1) {
#pragma unroll
    for (int j = 0; j < 8; j++) mma(e[j], af[j][0], af[j][1], af[j][2], af[j][3], b0, b1);
}
__device__ __forceinline__ void zero8(float (*e)[4]) {
#pragma unroll
    for (int j = 0; j < 8; j++) { e[j][0] = 0.f; e[j][1] = 0.f; e[j][2] = 0.f; e[j][3] = 0.f; }
}
#define PIN(x) asm volatile("" : "+r"(x))
#define PINL(x) asm volatile("" : "+l"(x))
__device__ __forceinline__ void sts(uint32_t addr, float v) { asm volatile("st.shared.f32 [%0], %1;" :: "r"(addr), "f"(v) : "memory"); }
__device__ __forceinline__ float4 lds4(uint32_t addr) {
    float4 v; asm volatile("ld.shared.v4.f32 {%0,%1,%2,%3}, [%4];" : "=f"(v.x), "=f"(v.y), "=f"(v.z), "=f"(v.w) : "r"(addr) : "memory"); return v;
}
__device__ __forceinline__ void store_part(float (*e)[4], uint32_t po, bool t0, bool t1) {
    const float l0 = t0 ? e[2][0] + e[3][1] : e[0][0] + e[1][1], h0 = t0 ? e[2][2] + e[3][3] : e[0][2] + e[1][3];
    const float l1 = t0 ? e[6][0] + e[7][1] : e[4][0] + e[5][1], h1 = t0 ? e[6][2] + e[7][3] : e[4][2] + e[5][3];
    sts(po, t1 ? l1 : l0); sts(po + 8 * 36 * 4, t1 ? h1 : h0);
}
__device__ __forceinline__ float rowsum32(uint32_t row) {
    const float4 a = lds4(row), b = lds4(row + 16), c = lds4(row + 32), d = lds4(row + 48), e = lds4(row + 64), f = lds4(row + 80), g = lds4(row + 96), h = lds4(row + 112);
    return ((sum4(a) + sum4(b)) + (sum4(c) + sum4(d))) + ((sum4(e) + sum4(f)) + (sum4(g) + sum4(h)));
}
template <class Set, class Issue, class Proc>
__device__ __forceinline__ void poll1(Set& sa, Issue issue, Proc proc, uint32_t (*af)[4], uint32_t tile, uint32_t bar, int lane) {
    bool have = false, bad = true;
#pragma unroll 1
    for (int it = 0; it < SPIN_MAX; it++) {
        if (bad) issue(sa);
        if (!have) { have = mbar_test(bar); if (have) frags(af, tile, lane); }
        bad = __any_sync(FULL, proc(sa));
        if (have && !bad) break;
    }
}
struct Set2 { uint4 a, b; };

struct Params {
    const __nv_bfloat16 *x, *kc, *vc, *wq, *wo, *w1, *w2;
    __nv_bfloat16* out;
    uint32_t* arena;
    float pf_t0, pf_pace, ld_t0, ld_pace, gap, gap2, sh1, sh2;
    int w2a;
};

__global__ void __launch_bounds__(NTHREADS, 1)
fused_decode_kernel(const __grid_constant__ Params P, const __grid_constant__ CUtensorMap map_v, const __grid_constant__ CUtensorMap map_wo,
                    const __grid_constant__ CUtensorMap map_w1, const __grid_constant__ CUtensorMap map_w2)
{
    extern __shared__ __align__(1024) unsigned char sm[];
    const int t = threadIdx.x, lane = t & 31, w = __shfl_sync(FULL, t >> 5, 0);
    const int c = blockIdx.x, h = c >> 2, r = c & 3;
    const uint32_t sb = (uint32_t)__cvta_generic_to_shared(sm);
    const uint32_t bars = sb + SM_BAR;
    const uint64_t pol = policy_evict_first();
    const int kg = c / 20, ng = c - kg * 20;
    const bool is_f1 = c >= F1_FIRST && c < F2_FIRST, is_f2 = c >= F2_FIRST;
    uint32_t* const A = P.arena;
    const int w2a = P.w2a;
    const size_t kv_off = ((size_t)h * SK + (SK - WIN)) * 256;

    if (w == 18) {
        const uint32_t tstart = gtime();
        uint32_t ep;
        uint32_t* po = A + a_o(0, c * 32 + perm16(lane)); PINL(po);
        {
            uint2 xs[5];
#pragma unroll
            for (int i = 0; i < 5; i++) xs[i] = __ldg((const uint2*)(P.x + lane * 4 + 128 * i));
            ep = ld_rlx1(A + A_EP);
            st_rlx1(po, 0u); st_rlx1(po + 1024, 0u);
            float s = 0.f;
#pragma unroll
            for (int i = 0; i < 5; i++) s += (bf_lo(xs[i].x) + bf_hi(xs[i].x)) + (bf_lo(xs[i].y) + bf_hi(xs[i].y));
#pragma unroll
            for (int m = 16; m; m >>= 1) s += shx(s, m);
            const float mean = s * (1.0f / D);
            float ss = 0.f;
#pragma unroll
            for (int i = 0; i < 5; i++) {
                float a = bf_lo(xs[i].x) - mean, b = bf_hi(xs[i].x) - mean, e = bf_lo(xs[i].y) - mean, f = bf_hi(xs[i].y) - mean;
                ss += (a * a + b * b) + (e * e + f * f);
            }
#pragma unroll
            for (int m = 16; m; m >>= 1) ss += shx(ss, m);
            const float mb = bfr(mean), rs = rcp_apx(bfr(sqrt_apx(bfr(bfr(ss * (1.0f / D)) + 1e-5f))));
#pragma unroll
            for (int i = 0; i < 5; i++) {
                const uint32_t d0 = pack2(bf_lo(xs[i].x) - mb, bf_hi(xs[i].x) - mb), d1 = pack2(bf_lo(xs[i].y) - mb, bf_hi(xs[i].y) - mb);
                *(uint2*)(sm + SM_XN + lane * 8 + i * 256) = make_uint2(pack2(bf_lo(d0) * rs, bf_hi(d0) * rs), pack2(bf_lo(d1) * rs, bf_hi(d1) * rs));
                *(uint2*)(sm + SM_X + lane * 8 + i * 256) = xs[i];
            }
            *(uint2*)(sm + SM_EP) = make_uint2(ep, 0u);
            bar_arrive(6, 544);
            TL(21);
        }
        const uint32_t tag = ep % 255u + 1u, e3 = ep % 3u + 1u, tag2 = ((e3 & 1u) << 15) | ((e3 & 2u) << 30);
        int side = 0;
        {
            uint32_t best[2] = {0xffffffffu, 0xffffffffu};
            if (lane == 0) { while ((int)(gtime() - tstart) < (int)PROBE_T) __nanosleep(200); }
            __syncwarp();
#pragma unroll 1
            for (int i = 0; i < 2; i++) {
#pragma unroll
                for (int k = 0; k < 2; k++) {
                    uint32_t c0 = clk32(), c1, old = 0;
                    if (lane == 0) asm volatile("atom.relaxed.gpu.global.exch.b32 %0, [%1], 0;" : "=r"(old) : "l"(po + k * 1024) : "memory");
                    asm volatile("{\n.reg .pred p;\nsetp.ne.u32 p, %1, 0;\n@p trap;\nmov.u32 %0, %%clock;\n}" : "=r"(c1) : "r"(old) : "memory");
                    best[k] = min(best[k], c1 - c0);
                }
            }
            side = __shfl_sync(FULL, best[1] < best[0], 0);
            ((volatile uint32_t*)(sm + SM_EP))[1] = side + 1;
            TL(22);
        }
        uint32_t row = sb + SM_RED + lane * 144; PIN(row);
        bar_sync(2, 544);
        { const uint32_t tv = pack2(0.f, rowsum32(row)) | tag; st_rlx1(po, tv); st_rlx1(po + 1024, tv); }
        TL(5);
        if (c < NO) {
            uint32_t* ph = A + a_hp(1, kg, ng * 32 + perm16(lane)); PINL(ph);
            bar_sync(3, 544);
            const uint32_t tv = tagw(rowsum32(row + (SM_PART2 - SM_RED)), tag);
            st_rlx1(ph, tv); st_rlx1(ph + 1024, tv);
            TL(8);
        }
        if (is_f1) {
            uint32_t* mbox = A + a_h1(lane & 1, (c - F1_FIRST) >> 2, ((c - F1_FIRST) & 3) * 16 + (perm16(lane) >> 1)); PINL(mbox);
            uint32_t sp = sb + SM_ST + (lane & 1) * 48, fp = sb + SM_FIN + lane * (FIN_PITCH * 4); PIN(sp); PIN(fp);
            bar_sync(4, 352);
            const float4 s0 = lds4(sp), s1 = lds4(sp + 16), s2 = lds4(sp + 32);
            const float4 a0 = lds4(fp), a1 = lds4(fp + 16), a2 = lds4(fp + 32), a3 = lds4(fp + 48), a4 = lds4(fp + 64), a5 = lds4(fp + 80);
            const float sa = (sum4(s0) + sum4(s1)) + (s2.x + s2.y), sb2 = shx(sa, 1);
            const float acc = (sum4(a0) + sum4(a1)) + (a2.x + a2.y), cs = (sum4(a3) + sum4(a4)) + (a5.x + a5.y);
            TLD(11, acc);
            const float mean = ((lane & 1) ? sa : sb2) * (1.0f / D);
            const float var = fmaxf(((lane & 1) ? sb2 : sa) * (1.0f / D) - mean * mean, 0.f);
            const float rs = rcp_apx(bfr(sqrt_apx(bfr(bfr(var) + 1e-5f))));
            const float hid = fmaxf((acc - bfr(mean) * cs) * rs, 0.f), oth = shx(hid, 1);
            st_rlx1(mbox, (((lane & 1) ? pack2(oth, hid) : pack2(hid, oth)) & 0x7fff7fffu) | tag2);
            TL(12);
        } else if (is_f2) {
            const int col = (c - F2_FIRST) * 16 + (lane & 15);
            unsigned short* op = (unsigned short*)P.out + col; PINL(op);
            uint32_t fp = sb + SM_PART2 + (lane & 15) * 240 + (lane >> 4) * 112; PIN(fp);
            const float xv = __uint_as_float((uint32_t)((const unsigned short*)(sm + SM_X))[col] << 16);
            const uint32_t* p = A + a_hp(side, (lane >> 4) * 2, perm16(col));
            uint32_t u0, u1; int it = 0;
            mbar_wait(bars + 8 * (B_WO + 2));
            while (u0 = ld_rlx1(p), u1 = ld_rlx1(p + 4096), __any_sync(FULL, ((u0 ^ tag) | (u1 ^ tag)) & 0xffu) && ++it < SPIN_MAX) delay(200);
            float hs = untag(u0) + untag(u1);
            hs += shx(hs, 16);
            const float hval = bfr(xv + bfr(hs));
            bar_sync(5, 480);
            const float4 a0 = lds4(fp), a1 = lds4(fp + 16), a2 = lds4(fp + 32), a3 = lds4(fp + 48), a4 = lds4(fp + 64), a5 = lds4(fp + 80), a6 = lds4(fp + 96);
            float sum = ((sum4(a0) + sum4(a1)) + (sum4(a2) + sum4(a3))) + ((sum4(a4) + sum4(a5)) + sum4(a6));
            sum += shx(sum, 16);
            if (lane < 16) *op = (unsigned short)pack2(hval + bfr(sum), 0.f);
            if (c == NCTA - 1 && lane == 0) st_rlx1(A + A_EP, ep + 1);
            TL(16);
        }
        return;
    }
    if (w == 17) {
        if (lane == 0) {
            const uint32_t t0 = gtime();
            float tt = P.pf_t0;
#pragma unroll 1
            for (int i = 0; i < 32; i++) {
                wait_until(t0, tt); tt += P.pf_pace;
                prefetch_l2((const char*)(i < 16 ? P.kc : P.vc) + (size_t)((((i >> 3) & 1) * 16 + (c >> 3)) * 32 + 24 + (i & 7)) * 32768 + (c & 7) * 4096, 4096);
            }
#pragma unroll 1
            for (int seg = 2; seg < 6; seg++) {
                const char* p; uint32_t stride, bytes; int n; float du;
                if (seg == 2) { p = (const char*)P.wo + (c >> 5) * 1310720 + (c & 31) * 5120; stride = 163840; bytes = 5120; n = 8; du = U_WO; }
                else if (seg == 4) { p = (const char*)P.w1 + c * 3456; stride = 442368; bytes = 3456; n = 5; du = U_W1; }
                else { p = (const char*)P.w2 + c * 2560 + (seg == 5 ? w2a * 327680 : 0); stride = 327680; bytes = 2560; n = seg == 5 ? (c < 96 ? 7 : 6) - w2a : w2a; du = U_W2; }
                du *= P.pf_pace;
                if (seg == 3) tt += P.gap;
                if (seg == 5) tt += P.gap2;
#pragma unroll 1
                for (int i = 0; i < n; i++) { wait_until(t0, tt); tt += du; prefetch_l2(p, bytes); p += stride; }
            }
            TL(29);
        }
        return;
    }
    if (w == 16) {
        const uint32_t t0 = gtime();
        TL(0);
        if (lane == 0) {
            asm volatile("prefetch.tensormap [%0];" :: "l"(&map_v) : "memory");
            asm volatile("prefetch.tensormap [%0];" :: "l"(is_f2 ? &map_w2 : &map_wo) : "memory");
            asm volatile("prefetch.tensormap [%0];" :: "l"(&map_w1) : "memory");
#pragma unroll
            for (int i = 0; i < NBAR; i++) mbar_init(bars + 8 * i, 1);
            asm volatile("fence.mbarrier_init.release.cluster;" ::: "memory");
        }
        __syncwarp();
        bar_arrive(1, 544);
        if (lane == 0) {
            const float pace = P.ld_pace;
            float tt = P.ld_t0 + (h >> 4) * 8 * pace;
#pragma unroll 1
            for (int i = 0; i < 8; i++) {
                wait_until(t0, tt + i * pace);
                uint32_t b = bars + 8 * (B_K + (i >> 1));
                if (!(i & 1)) mbar_expect_tx(b, 16384);
                bulk_g2s(sb + SM_K + i * 8192, (const char*)P.kc + kv_off + i * 32768 + r * 8192, 8192, b, pol);
            }
#pragma unroll 1
            for (int i = 0; i < 8; i++) {
                wait_until(t0, tt + (16 + i) * pace);
                uint32_t b = bars + 8 * (B_V + i);
                mbar_expect_tx(b, 8192);
                tma2d(sb + SM_V + i * 8192, &map_v, r * 32, h * SK + (SK - WIN) + i * 128, b, pol);
            }
            tt = P.ld_t0 + 32 * pace;
            if (c < NO) {
#pragma unroll 1
                for (int i = 0; i < 8; i++) {
                    wait_until(t0, tt + i * (pace * U_WO));
                    uint32_t b = bars + 8 * (B_WO + i);
                    mbar_expect_tx(b, 8192);
                    tma2d(sb + SM_WO + i * 8192, &map_wo, ng * 32, kg * 1024 + i * 128, b, pol);
                }
            }
            tt += pace * (8 * U_WO) + P.gap;
            if (is_f1) {
                mbar_wait(bars + 8 * B_KFREE);
#pragma unroll 1
                for (int i = 0; i < 5; i++) {
                    wait_until(t0, tt - P.sh1 + (w2a * U_W2 + i * U_W1) * pace);
                    uint32_t b = bars + 8 * (B_W1 + i);
                    mbar_expect_tx(b, 8192);
                    tma2d(sb + SM_K + i * 8192, &map_w1, (c - F1_FIRST) * 32, i * 128, b, pol);
                }
            } else if (is_f2) {
#pragma unroll 1
                for (int i = 0; i < 7; i++) {
                    wait_until(t0, tt - P.sh2 + i * U_W2 * pace + (i < w2a ? 0.f : 5 * U_W1 * pace + P.gap2));
                    uint32_t b = bars + 8 * (B_WO + i);
                    mbar_expect_tx(b, 8192);
                    tma2d(sb + SM_WO + i * 8192, &map_w2, (c - F2_FIRST) * 16, i * 256, b, pol);
                }
            }
            TL(30);
        }
        return;
    }

    float* red = (float*)(sm + SM_RED);
    float* mw = (float*)(sm + SM_MW);
    float* lw = (float*)(sm + SM_LW);
    const int g = lane >> 2, tq = lane & 3;
    const int selsh = (g & 1) << 4;

    uint4 wv[5];
    const int row0 = r * 160 + (w >> 1) * 20 + tq;
    {
        const char* src = (const char*)P.wq + (size_t)row0 * (NH * DH * 2) + h * 256 + (w & 1) * 128 + g * 16;
#pragma unroll
        for (int i = 0; i < 5; i++) wv[i] = ldg_stream(src + (size_t)i * 4 * (NH * DH * 2), pol);
    }

    {
        int o = -1;
        if (w < 4) o = A_QX + c * 128 + t;
        else if (w < 12) o = A_SX + h * WIN + (w - 4) * 128 + r * 32 + lane;
        else if (w < 14) { if (c < NO) o = a_hp(w - 12, kg, ng * 32 + lane); }
        else if (w == 14) { if (is_f1) o = a_h1(lane >> 4, (c - F1_FIRST) >> 2, ((c - F1_FIRST) & 3) * 16 + (lane & 15)); }
        if (o >= 0) st_rlx1(A + o, 0u);
    }
    uint32_t epoch, tag, tag2;
    {
        bar_sync(6, 544);
        uint32_t bs[5];
#pragma unroll
        for (int i = 0; i < 5; i++) bs[i] = (uint32_t)((const unsigned short*)(sm + SM_XN))[row0 + 4 * i] << selsh;
        if (w == 5) TLD(23, __uint_as_float(wv[0].x));
        if (w == 5) TLD(24, __uint_as_float(wv[4].x ^ wv[3].x ^ wv[2].x ^ wv[1].x));
        float d1[4] = {0.f, 0.f, 0.f, 0.f}, d2[4] = {0.f, 0.f, 0.f, 0.f};
        mma(d1, wv[0].x, wv[0].y, wv[1].x, wv[1].y, bs[0], bs[1]); mma(d2, wv[0].z, wv[0].w, wv[1].z, wv[1].w, bs[0], bs[1]);
        mma(d1, wv[2].x, wv[2].y, wv[3].x, wv[3].y, bs[2], bs[3]); mma(d2, wv[2].z, wv[2].w, wv[3].z, wv[3].w, bs[2], bs[3]);
        mma(d1, wv[4].x, wv[4].y, 0u, 0u, bs[4], 0u);              mma(d2, wv[4].z, wv[4].w, 0u, 0u, bs[4], 0u);
        if (tq < 2) *(float4*)(red + (w >> 1) * 128 + (w & 1) * 64 + g * 8 + tq * 4) =
            tq ? make_float4(d2[0], d2[1], d2[2], d2[3]) : make_float4(d1[0], d1[1], d1[2], d1[3]);
        bar_sync(1, 544);
        epoch = *(volatile uint32_t*)(sm + SM_EP);
        tag = epoch % 255u + 1u;
        { const uint32_t e3 = epoch % 3u + 1u; tag2 = ((e3 & 1u) << 15) | ((e3 & 2u) << 30); }
        if (w < 4) {
            float s2 = 0.f;
#pragma unroll
            for (int i = 0; i < 8; i++) s2 += red[i * 128 + t];
            if (w == 0) TLD(1, s2);
            st_rlx1(A + A_QX + c * 128 + t, tagw(s2, tag));
            const uint32_t* p = A + A_QX + h * 512 + t;
            uint4 v; int it = 0;
            do { v.x = ld_rlx1(p); v.y = ld_rlx1(p + 128); v.z = ld_rlx1(p + 256); v.w = ld_rlx1(p + 384); } while (__any_sync(FULL, bad4(v, tag)) && ++it < SPIN_MAX);
            ((unsigned short*)(sm + SM_QS))[t] = (unsigned short)pack2((untag(v.x) + untag(v.y)) + (untag(v.z) + untag(v.w)), 0.f);
        }
        bar_sync(1, 512);
    }

    int side;
    const bool tb0 = tq & 1, tb1 = tq & 2;
    uint32_t po = sb + SM_RED + (((tq >> 1) * 16 + g) * 36 + w * 2 + (tq & 1)) * 4;
    {
        const int ch0 = ((g & 1) * 4 + tq) * 16, ch1 = ch0 ^ 64;
        const uint4 q00 = *(const uint4*)(sm + SM_QS + ch0), q01 = *(const uint4*)(sm + SM_QS + ch1);
        const uint4 q10 = *(const uint4*)(sm + SM_QS + 128 + ch0), q11 = *(const uint4*)(sm + SM_QS + 128 + ch1);
        if (w == 0) TLD(2, __uint_as_float(q11.w));
        mbar_wait(bars + 8 * (B_K + (w >> 2)));
        if (w == 15) TL(3);
        const unsigned char* kp = sm + SM_K + (w * 16 + g) * 256;
        float sa[4] = {0.f, 0.f, 0.f, 0.f}, sb2[4] = {0.f, 0.f, 0.f, 0.f};
#define SCORE_STEP(off, Q) { const uint4 X = *(const uint4*)(kp + (off)), Y = *(const uint4*)(kp + 2048 + (off)); \
        mma(sa, X.x, Y.x, X.y, Y.y, Q.x, Q.y); mma(sb2, X.z, Y.z, X.w, Y.w, Q.z, Q.w); }
        SCORE_STEP(ch0, q00) SCORE_STEP(ch1, q01) SCORE_STEP(128 + ch0, q10) SCORE_STEP(128 + ch1, q11)
        float s0 = (g & 1) ? sa[1] + sb2[1] : sa[0] + sb2[0];
        float s1 = (g & 1) ? sa[3] + sb2[3] : sa[2] + sb2[2];
        s0 = bfr(bfr(s0) * 0.08838834764831845f);
        s1 = bfr(bfr(s1) * 0.08838834764831845f);
        if (tq < 2) st_rlx1(A + A_SX + h * WIN + (w >> 1) * 128 + r * 32 + (w & 1) * 16 + perm16(g + 8 * tq), __float_as_uint(tq ? s1 : s0) | tag);
        if (w == 15) TL(17);
        uint4 v;
        delay(SC_DELAY);
        poll4<1, 0, SC_BACKOFF>(&v, A + A_SX + h * WIN + w * 64 + (lane & 15) * 4, tag);
        float e0 = bf_hi(v.x), e1 = bf_hi(v.y), e2 = bf_hi(v.z), e3 = bf_hi(v.w);
        float m = fmaxf(fmaxf(e0, e1), fmaxf(e2, e3));
        m = fmaxf(m, shx(m, 1)); m = fmaxf(m, shx(m, 2)); m = fmaxf(m, shx(m, 4)); m = fmaxf(m, shx(m, 8));
        if (lane == 0) mw[w] = m;
        bar_sync(1, 512);
        if (t == 0) mbar_arrive(bars + 8 * B_KFREE);
        float M = mw[lane & 15];
        M = fmaxf(M, shx(M, 1)); M = fmaxf(M, shx(M, 2)); M = fmaxf(M, shx(M, 4)); M = fmaxf(M, shx(M, 8));
        e0 = ex2((e0 - M) * LOG2E); e1 = ex2((e1 - M) * LOG2E); e2 = ex2((e2 - M) * LOG2E); e3 = ex2((e3 - M) * LOG2E);
        float l = (e0 + e1) + (e2 + e3);
        l += shx(l, 1); l += shx(l, 2); l += shx(l, 4); l += shx(l, 8);
        if (lane == 0) lw[w] = l;
        bar_sync(1, 512);
        float L = lw[lane & 15];
        L += shx(L, 1); L += shx(L, 2); L += shx(L, 4); L += shx(L, 8);
        L = rcp_apx(L);
        const uint32_t b0 = pack2(e0 * L, e1 * L), b1 = pack2(e2 * L, e3 * L);
        if (w == 15) TLD(19, __uint_as_float(b0));
        mbar_wait(bars + 8 * (B_V + (w >> 1)));
        if (w == 15) TL(4);
        uint32_t af[8][4]; float e[8][4];
        frags(af, sb + SM_V + w * 4096, lane); zero8(e); mma8(e, af, b0, b1); store_part(e, po, tb0, tb1);
        bar_arrive(2, 544);
    }
    po += SM_PART2 - SM_RED; PIN(po);
    { int it = 0; while ((side = ((volatile uint32_t*)(sm + SM_EP))[1]) == 0 && ++it < SPIN_MAX) {} side = __shfl_sync(FULL, side, 0) > 1; }

    if (c < NO) {
        const uint32_t* p = A + a_o(side, kg * 1024 + w * 64 + (lane & 15) * 4);
        uint4 va; uint32_t b0, b1;
        uint32_t af[8][4]; float e[8][4];
        mbar_wait(bars + 8 * (B_WO + (w >> 2)));
        poll1(va, [&](uint4& v) { v = ld_rlx4(p); },
              [&](const uint4& v) { b0 = __byte_perm(v.x, v.y, 0x7632); b1 = __byte_perm(v.z, v.w, 0x7632); return bad4(v, tag); },
              af, sb + SM_WO + w * 4096, bars + 8 * (B_WO + (w >> 1)), lane);
        if (w == 15) TL(7);
        zero8(e); mma8(e, af, b0, b1); store_part(e, po, tb0, tb1);
        bar_arrive(3, 544);
    }

    if (is_f1) {
        if (w < 10) {
            const uint32_t* xp = (const uint32_t*)(sm + SM_X) + w * 32 + (g & 3) * 8 + tq;
            const float x0 = bf_lo(xp[0]), x1 = bf_hi(xp[0]), x2 = bf_lo(xp[4]), x3 = bf_hi(xp[4]);
            uint32_t fo = sb + SM_FIN + ((16 * (tq & 1) + g) * FIN_PITCH + (tq >> 1) * 12 + w) * 4; PIN(fo);
            uint32_t so = sb + SM_ST + ((lane >> 1) * 12 + w) * 4; PIN(so);
            const bool stv = g < 4 && (tq & 1) == (g >> 1);
            const uint32_t* p = A + a_hp(side, (lane >> 4) * 2, w * 64 + (lane & 15) * 4);
            mbar_wait(bars + 8 * B_W1);
            uint32_t af[8][4], b0, b1;
            Set2 va;
            poll1(va, [&](Set2& v) { v.a = ld_rlx4(p); v.b = ld_rlx4(p + 4096); },
                  [&](const Set2& v) {
                      const uint32_t y0 = v.a.x ^ tag, y1 = v.a.y ^ tag, y2 = v.a.z ^ tag, y3 = v.a.w ^ tag, z0 = v.b.x ^ tag, z1 = v.b.y ^ tag, z2 = v.b.z ^ tag, z3 = v.b.w ^ tag;
                      float s0 = __uint_as_float(y0) + __uint_as_float(z0), s1 = __uint_as_float(y1) + __uint_as_float(z1);
                      float s2 = __uint_as_float(y2) + __uint_as_float(z2), s3 = __uint_as_float(y3) + __uint_as_float(z3);
                      s0 += shx(s0, 16); s1 += shx(s1, 16); s2 += shx(s2, 16); s3 += shx(s3, 16);
                      b0 = pack2(x0 + bfr(s0), x1 + bfr(s1)); b1 = pack2(x2 + bfr(s2), x3 + bfr(s3));
                      if (g >= 4) { b0 = 0x3f803f80u; b1 = 0x3f803f80u; }
                      return ((y0 | y1 | y2) | (y3 | z0 | z1) | (z2 | z3)) & 0xffu;
                  },
                  af, sb + SM_K + w * 4096, bars + 8 * (B_W1 + (w >> 1)), lane);
            if (w == 9) TL(10);
            float e[8][4], gm[4] = {0.f, 0.f, 0.f, 0.f};
            mma(gm, b0, 0u, b1, 0u, b0, b1);
            zero8(e); mma8(e, af, b0, b1);
            float st = stv ? ((g & 1) ? gm[1] : gm[0]) : 0.f;
            st += shx(st, 4);
            const float l0 = tb0 ? e[2][0] + e[3][1] : e[0][0] + e[1][1], h0 = tb0 ? e[2][2] + e[3][3] : e[0][2] + e[1][3];
            const float l1 = tb0 ? e[6][0] + e[7][1] : e[4][0] + e[5][1], h1 = tb0 ? e[6][2] + e[7][3] : e[4][2] + e[5][3];
            st += shx(st, 9);
            sts(fo, (tb0 ? l1 : l0) + shx(tb0 ? l0 : l1, 1));
            sts(fo + 8 * FIN_PITCH * 4, (tb0 ? h1 : h0) + shx(tb0 ? h0 : h1, 1));
            if (!(lane & 29)) sts(so, st);
            bar_arrive(4, 352);
        }
    } else if (is_f2) {
        if (w < 14) {
            const bool live = w < 13 || lane < 16;
            const uint32_t* p = A + a_h1(side, w, (live ? lane : lane - 16) * 2);
            const uint32_t msk = live ? 0x7fff7fffu : 0u;
            uint32_t qo = sb + SM_PART2 + (g * 60 + w * 4 + tq) * 4; PIN(qo);
            const uint32_t ad = sb + SM_WO + w * 4096 + ((lane & 7) + 8 * (lane >> 4)) * 32 + ((((lane >> 3) ^ (lane >> 2)) & 1) << 4);
            const uint32_t bar = bars + 8 * (B_WO + (w >> 1));
            mbar_wait(bars + 8 * (B_WO + 3));
            uint32_t af[8][4]; uint2 v;
            bool have = false, bad = true;
#pragma unroll 1
            for (int it = 0; it < SPIN_MAX; it++) {
                if (bad) v = ld_rlx2(p);
                if (!have) {
                    have = mbar_test(bar);
                    if (have) {
#pragma unroll
                        for (int j = 0; j < 8; j++) ldsm4t(af[j], ad + j * 512);
                    }
                }
                bad = __any_sync(FULL, ((v.x ^ tag2) | (v.y ^ tag2)) & 0x80008000u);
                if (have && !bad) break;
            }
            if (w == 0) TL(14);
            float e[8][4];
            zero8(e);
            mma8(e, af, v.x & msk, v.y & msk);
            const float l0 = tb0 ? e[2][0] + e[3][1] : e[0][0] + e[1][1], h0 = tb0 ? e[2][2] + e[3][3] : e[0][2] + e[1][3];
            const float l1 = tb0 ? e[6][0] + e[7][1] : e[4][0] + e[5][1], h1 = tb0 ? e[6][2] + e[7][3] : e[4][2] + e[5][3];
            sts(qo, tb1 ? l1 : l0); sts(qo + 8 * 240, tb1 ? h1 : h0);
            bar_arrive(5, 480);
        }
    }
}

typedef CUresult (*EncodeFn)(CUtensorMap*, CUtensorMapDataType, cuuint32_t, void*, const cuuint64_t*, const cuuint64_t*,
                             const cuuint32_t*, const cuuint32_t*, CUtensorMapInterleave, CUtensorMapSwizzle,
                             CUtensorMapL2promotion, CUtensorMapFloatOOBfill);
float g_par[9] = {PF_T0, PF_PACE, LD_T0, LD_PACE, 400.f, 0.f, 0.f, 0.f, 0.f};

void make_map(EncodeFn enc, CUtensorMap* m, void* base, int cols, int rows, int bc, int br, CUtensorMapSwizzle sw = CU_TENSOR_MAP_SWIZZLE_64B) {
    cuuint64_t gd[2] = {(cuuint64_t)cols, (cuuint64_t)rows}; cuuint64_t gs[1] = {(cuuint64_t)cols * 2};
    cuuint32_t bd[2] = {(cuuint32_t)bc, (cuuint32_t)br}; cuuint32_t es[2] = {1, 1};
    enc(m, CU_TENSOR_MAP_DATA_TYPE_BFLOAT16, 2, base, gd, gs, bd, es, CU_TENSOR_MAP_INTERLEAVE_NONE, sw,
        CU_TENSOR_MAP_L2_PROMOTION_L2_128B, CU_TENSOR_MAP_FLOAT_OOB_FILL_NONE);
}

}

extern "C" void kernel_launch(void* const* d_in, const int* in_sizes, int n_in, void* d_out, int out_size) {
    (void)in_sizes; (void)n_in; (void)out_size;
    static EncodeFn enc = nullptr;
    static uint32_t* arena = nullptr;
    if (!enc) {
        void* sym = nullptr;
        cudaGetSymbolAddress(&sym, g_arena);
        arena = (uint32_t*)(((uintptr_t)sym + 65535) & ~(uintptr_t)65535);
        cudaDriverEntryPointQueryResult qr;
        cudaGetDriverEntryPoint("cuTensorMapEncodeTiled", (void**)&enc, cudaEnableDefault, &qr);
        cudaFuncSetAttribute(fused_decode_kernel, cudaFuncAttributeMaxDynamicSharedMemorySize, SM_TOTAL);
    }
    CUtensorMap mv, mwo, mw1, mw2;
    make_map(enc, &mv, d_in[2], DH, NH * SK, 32, 128);
    make_map(enc, &mwo, d_in[4], D, NH * DH, 32, 128);
    make_map(enc, &mw1, d_in[6], DFF, D, 32, 128);
    make_map(enc, &mw2, d_in[7], D, DFF, 16, 256, CU_TENSOR_MAP_SWIZZLE_32B);
    Params P = {(const __nv_bfloat16*)d_in[0], (const __nv_bfloat16*)d_in[1], (const __nv_bfloat16*)d_in[2], (const __nv_bfloat16*)d_in[3],
                (const __nv_bfloat16*)d_in[4], (const __nv_bfloat16*)d_in[6], (const __nv_bfloat16*)d_in[7], (__nv_bfloat16*)d_out, arena,
                g_par[0], g_par[1], g_par[2], g_par[3], g_par[4], g_par[6], g_par[7], g_par[8], (int)g_par[5]};
    fused_decode_kernel<<<NCTA, NTHREADS, SM_TOTAL, cudaStreamPerThread>>>(P, mv, mwo, mw1, mw2);
}
```

```cpp
#include <cuda_runtime.h>
#include <cuda_bf16.h>
#include <cuda.h>
#include <stdint.h>

namespace {

constexpr int D = 640, DH = 128, NH = 32, SK = 4096, WIN = 1024, DFF = 1728;
constexpr int NCTA = 128;
constexpr int NTHREADS = 608;

#define NGK 2
#define NGV 2
#define BOX_SP 70
constexpr int PROBE_T = 2500;
constexpr int SC_DELAY = 300, SC_BACKOFF = 100;

constexpr int FIN_PITCH = 28;
constexpr int SM_K = 0;
constexpr int SM_V = 65536;
constexpr int SM_WO = 131072;
constexpr int SM_RED = SM_WO + 65536;
constexpr int SM_PART2 = SM_RED + 32 * 36 * 4;
constexpr int SM_FIN = SM_PART2 + 32 * 36 * 4;
constexpr int SM_ST = SM_FIN + 32 * FIN_PITCH * 4;
constexpr int SM_QS = SM_ST + 96;
constexpr int SM_X = SM_QS + 256;
constexpr int SM_XN = SM_X + 1280;
constexpr int SM_MW = SM_XN + 1280;
constexpr int SM_LW = SM_MW + 64;
constexpr int SM_BAR = SM_LW + 64;
constexpr int SM_EP = SM_BAR + 256;
constexpr int SM_TAB = SM_EP + 32;
constexpr int SM_TOTAL = SM_TAB + 512;

constexpr int B_K = 0, B_V = 8, B_WO = 16, B_W1 = 24, B_KFREE = 29, NBAR = 30;
constexpr int NSTEP = 52;
constexpr int SPIN_MAX = 1 << 20;
constexpr unsigned FULL = 0xffffffffu;
constexpr float LOG2E = 1.4426950408889634f;

constexpr int A_QX = 16384;
constexpr int A_SX = A_QX + NCTA * 128;
constexpr int A_EP = A_SX + NH * WIN;
constexpr int A_WORDS = A_EP + 32;
__device__ uint32_t g_arena[A_WORDS + 16384];
__device__ __forceinline__ int a_o(int s, int head, int i) { return (head & 3) * 4096 + s * 1024 + (head >> 2) * 128 + i; }
__device__ __forceinline__ int a_hp(int s, int k, int i) { return k * 4096 + (3 - s) * 1024 + i; }
__device__ __forceinline__ int a_h1(int s, int tile, int i) { return (tile >> 2) * 4096 + (3 - s) * 1024 + D + (tile & 3) * 64 + i; }
#define TL(slot) do {} while (0)
#define TLD(slot, dep) do {} while (0)

__device__ __forceinline__ uint32_t gtime() { uint32_t t; asm volatile("mov.u32 %0, %%globaltimer_lo;" : "=r"(t) :: "memory"); return t; }
__device__ __forceinline__ uint32_t clk32() { uint32_t t; asm volatile("mov.u32 %0, %%clock;" : "=r"(t) :: "memory"); return t; }
__device__ __forceinline__ uint32_t pack2(float lo, float hi) { uint32_t d; asm("cvt.rn.bf16x2.f32 %0, %1, %2;" : "=r"(d) : "f"(hi), "f"(lo)); return d; }
__device__ __forceinline__ float bfr(float x) { return __uint_as_float(pack2(0.f, x)); }
__device__ __forceinline__ float bf_lo(uint32_t w) { return __uint_as_float(w << 16); }
__device__ __forceinline__ float bf_hi(uint32_t w) { return __uint_as_float(w & 0xffff0000u); }
__device__ __forceinline__ uint32_t tagw(float v, uint32_t tag) { return (__float_as_uint(v) & 0xffffff00u) | tag; }
__device__ __forceinline__ float untag(uint32_t w) { return __uint_as_float(w & 0xffffff00u); }
__device__ __forceinline__ uint32_t bad4(const uint4& v, uint32_t tag) { return ((v.x ^ tag) | (v.y ^ tag) | (v.z ^ tag) | (v.w ^ tag)) & 0xffu; }
__device__ __forceinline__ int perm16(int i) { return (i & ~15) | ((i & 6) << 1) | ((i & 8) >> 2) | (i & 1); }

__device__ __forceinline__ void mbar_init(uint32_t bar, uint32_t cnt) { asm volatile("mbarrier.init.shared::cta.b64 [%0], %1;" :: "r"(bar), "r"(cnt) : "memory"); }
__device__ __forceinline__ void mbar_expect_tx(uint32_t bar, uint32_t bytes) { asm volatile("mbarrier.arrive.expect_tx.shared::cta.b64 _, [%0], %1;" :: "r"(bar), "r"(bytes) : "memory"); }
__device__ __forceinline__ void mbar_arrive(uint32_t bar) { asm volatile("mbarrier.arrive.shared::cta.b64 _, [%0];" :: "r"(bar) : "memory"); }
__device__ __forceinline__ void mbar_wait(uint32_t bar) {
    uint32_t done; int it = 0;
    do {
        asm volatile("{\n.reg .pred p;\nmbarrier.try_wait.parity.shared::cta.b64 p, [%1], 0, 20000;\nselp.u32 %0, 1, 0, p;\n}" : "=r"(done) : "r"(bar) : "memory");
    } while (!done && ++it < SPIN_MAX);
}
__device__ __forceinline__ bool mbar_test(uint32_t bar) {
    uint32_t done;
    asm volatile("{\n.reg .pred p;\nmbarrier.test_wait.parity.shared::cta.b64 p, [%1], 0;\nselp.u32 %0, 1, 0, p;\n}" : "=r"(done) : "r"(bar) : "memory");
    return __all_sync(0xffffffffu, done);
}
__device__ __forceinline__ uint64_t policy_evict_first() { uint64_t p; asm("createpolicy.fractional.L2::evict_first.b64 %0, 1.0;" : "=l"(p)); return p; }
__device__ __forceinline__ void bulk_g2s(uint32_t dst, const void* src, uint32_t bytes, uint32_t bar) {
    asm volatile("cp.async.bulk.shared::cluster.global.mbarrier::complete_tx::bytes [%0], [%1], %2, [%3];" :: "r"(dst), "l"(src), "r"(bytes), "r"(bar) : "memory");
}
__device__ __forceinline__ void tma2d(uint32_t dst, const CUtensorMap* m, int c0, int c1, uint32_t bar) {
    asm volatile("cp.async.bulk.tensor.2d.shared::cluster.global.mbarrier::complete_tx::bytes [%0], [%1, {%3, %4}], [%2];" :: "r"(dst), "l"(m), "r"(bar), "r"(c0), "r"(c1) : "memory");
}
__device__ __forceinline__ void prefetch_l2(const void* src, uint32_t bytes) {
    asm volatile("cp.async.bulk.prefetch.L2.global.L2::cache_hint [%0], %1, %2;" :: "l"(src), "r"(bytes), "l"(policy_evict_first()) : "memory");
}
__device__ __forceinline__ void wait_until(uint32_t tgt) {
    int it = 0;
    while ((int)(gtime() - tgt) < 0 && ++it < SPIN_MAX) {}
}
__device__ __forceinline__ void bar_sync(int id, int n) { asm volatile("bar.sync %0, %1;" :: "r"(id), "r"(n) : "memory"); }
__device__ __forceinline__ void bar_arrive(int id, int n) { asm volatile("bar.arrive %0, %1;" :: "r"(id), "r"(n) : "memory"); }
__device__ __forceinline__ uint4 ld_rlx4(const void* p) {
    uint4 v; asm volatile("ld.relaxed.gpu.global.v4.u32 {%0,%1,%2,%3}, [%4];" : "=r"(v.x), "=r"(v.y), "=r"(v.z), "=r"(v.w) : "l"(p) : "memory"); return v;
}
__device__ __forceinline__ uint2 ld_rlx2(const void* p) {
    uint2 v; asm volatile("ld.relaxed.gpu.global.v2.u32 {%0,%1}, [%2];" : "=r"(v.x), "=r"(v.y) : "l"(p) : "memory"); return v;
}
__device__ __forceinline__ uint32_t ld_rlx1(const void* p) {
    uint32_t v; asm volatile("ld.relaxed.gpu.global.u32 %0, [%1];" : "=r"(v) : "l"(p) : "memory"); return v;
}
__device__ __forceinline__ void st_rlx1(void* p, uint32_t v) { asm volatile("st.relaxed.gpu.global.u32 [%0], %1;" :: "l"(p), "r"(v) : "memory"); }
__device__ __forceinline__ float sqrt_apx(float x) { float y; asm("sqrt.approx.f32 %0, %1;" : "=f"(y) : "f"(x)); return y; }
__device__ __forceinline__ float ex2(float x) { float y; asm("ex2.approx.ftz.f32 %0, %1;" : "=f"(y) : "f"(x)); return y; }
__device__ __forceinline__ float rcp_apx(float x) { float y; asm("rcp.approx.ftz.f32 %0, %1;" : "=f"(y) : "f"(x)); return y; }
__device__ __forceinline__ float shx(float v, int m) { return __shfl_xor_sync(FULL, v, m); }
__device__ __forceinline__ void delay(uint32_t n) { uint32_t t0 = clk32(); while (clk32() - t0 < n) {} }
__device__ __forceinline__ float sum4(const float4& a) { return (a.x + a.y) + (a.z + a.w); }

__device__ __forceinline__ void mma(float* d, uint32_t a0, uint32_t a1, uint32_t a2, uint32_t a3, uint32_t b0, uint32_t b1) {
    asm("mma.sync.aligned.m16n8k16.row.col.f32.bf16.bf16.f32 {%0,%1,%2,%3}, {%4,%5,%6,%7}, {%8,%9}, {%0,%1,%2,%3};"
        : "+f"(d[0]), "+f"(d[1]), "+f"(d[2]), "+f"(d[3]) : "r"(a0), "r"(a1), "r"(a2), "r"(a3), "r"(b0), "r"(b1));
}
__device__ __forceinline__ void ldsm4t(uint32_t* r, uint32_t addr) {
    asm volatile("ldmatrix.sync.aligned.m8n8.x4.trans.shared.b16 {%0,%1,%2,%3}, [%4];" : "=r"(r[0]), "=r"(r[1]), "=r"(r[2]), "=r"(r[3]) : "r"(addr) : "memory");
}
template <bool W64>
__device__ __forceinline__ void frags(uint32_t (*af)[4], uint32_t tile, int lane) {
    const int row = (lane & 7) + 8 * (lane >> 4);
    if (W64) {
        const uint32_t ad = tile + row * 64 + ((((lane >> 3) & 1) ^ ((lane >> 1) & 3)) << 4);
#pragma unroll
        for (int j = 0; j < 8; j++) ldsm4t(af[j], (ad ^ ((j >> 2) << 5)) + (j & 3) * 1024);
    } else {
        const uint32_t ad = tile + row * 32 + ((((lane >> 3) ^ (lane >> 2)) & 1) << 4);
#pragma unroll
        for (int j = 0; j < 8; j++) ldsm4t(af[j], ad + j * 512);
    }
}
__device__ __forceinline__ void mma8(float (*e)[4], const uint32_t (*af)[4], uint32_t b0, uint32_t b1) {
#pragma unroll
    for (int j = 0; j < 8; j++) mma(e[j], af[j][0], af[j][1], af[j][2], af[j][3], b0, b1);
}
__device__ __forceinline__ void zero8(float (*e)[4]) {
#pragma unroll
    for (int j = 0; j < 8; j++) { e[j][0] = 0.f; e[j][1] = 0.f; e[j][2] = 0.f; e[j][3] = 0.f; }
}
#define PIN(x) asm volatile("" : "+r"(x))
#define PINL(x) asm volatile("" : "+l"(x))
__device__ __forceinline__ void sts(uint32_t addr, float v) { asm volatile("st.shared.f32 [%0], %1;" :: "r"(addr), "f"(v) : "memory"); }
__device__ __forceinline__ float4 lds4(uint32_t addr) {
    float4 v; asm volatile("ld.shared.v4.f32 {%0,%1,%2,%3}, [%4];" : "=f"(v.x), "=f"(v.y), "=f"(v.z), "=f"(v.w) : "r"(addr) : "memory"); return v;
}
__device__ __forceinline__ void store_part(float (*e)[4], uint32_t po, bool t0, bool t1) {
    const float l0 = t0 ? e[2][0] + e[3][1] : e[0][0] + e[1][1], h0 = t0 ? e[2][2] + e[3][3] : e[0][2] + e[1][3];
    const float l1 = t0 ? e[6][0] + e[7][1] : e[4][0] + e[5][1], h1 = t0 ? e[6][2] + e[7][3] : e[4][2] + e[5][3];
    sts(po, t1 ? l1 : l0); sts(po + 8 * 36 * 4, t1 ? h1 : h0);
}
__device__ __forceinline__ float rowsum32(uint32_t row) {
    const float4 a = lds4(row), b = lds4(row + 16), c = lds4(row + 32), d = lds4(row + 48), e = lds4(row + 64), f = lds4(row + 80), g = lds4(row + 96), h = lds4(row + 112);
    return ((sum4(a) + sum4(b)) + (sum4(c) + sum4(d))) + ((sum4(e) + sum4(f)) + (sum4(g) + sum4(h)));
}
template <bool W64, class Set, class Issue, class Proc>
__device__ __forceinline__ void poll1(Set& sa, Issue issue, Proc proc, uint32_t (*af)[4], uint32_t tile, uint32_t bar, int lane) {
    bool have = false, bad = true;
#pragma unroll 1
    for (int it = 0; it < SPIN_MAX; it++) {
        if (bad) issue(sa);
        if (!have) { have = mbar_test(bar); if (have) frags<W64>(af, tile, lane); }
        if (bad) bad = __any_sync(FULL, proc(sa));
        if (have && !bad) break;
    }
}
template <int NG> __device__ __forceinline__ uint32_t kv_pf_off(int i, int c) {
    constexpr int S = 16 / NG, PP = 64 / S;
    const int k = c / PP, head = k * NG + i / S;
    return head * 256 + 192 + ((i + k) % S) * PP + c % PP;
}
template <int NG> __device__ __forceinline__ int kv_box(int i, int h) { constexpr int S = 16 / NG; return (i + (h / NG) * (8 / S)) & 7; }
template <int NG> __device__ __forceinline__ int kv_step(int i, int h) { constexpr int S = 16 / NG; return (h % NG) * S + i * S / 8; }
template <int NG> __device__ __forceinline__ int kv_sub(int i) { constexpr int S = 16 / NG; return (i % (8 / S)) * BOX_SP; }
struct Set2 { uint4 a, b; };

struct Params {
    const __nv_bfloat16 *x, *kc, *vc, *wq, *wo, *w1, *w2;
    __nv_bfloat16* out;
    uint32_t* arena;
    uint32_t pf[NSTEP], ld[NSTEP];
};

__global__ void __launch_bounds__(NTHREADS, 1)
fused_decode_kernel(const __grid_constant__ Params P, const __grid_constant__ CUtensorMap map_v, const __grid_constant__ CUtensorMap map_wo,
                    const __grid_constant__ CUtensorMap map_w1, const __grid_constant__ CUtensorMap map_w2)
{
    extern __shared__ __align__(1024) unsigned char sm[];
    const int t = threadIdx.x, lane = t & 31;
    const int c = blockIdx.x, h = c >> 2, r = c & 3;
    uint4 wv[5];
    const int row0 = r * 160 + (t >> 6) * 20 + (t & 3);
    if (t < 512) {
        const char* src = (const char*)P.wq + (size_t)row0 * (NH * DH * 2) + h * 256 + (t & 60) * 4;
#pragma unroll
        for (int i = 0; i < 5; i++)
            asm volatile("ld.global.nc.L1::no_allocate.L2::cache_hint.v4.u32 {%0,%1,%2,%3}, [%4], %5;" : "=r"(wv[i].x), "=r"(wv[i].y), "=r"(wv[i].z), "=r"(wv[i].w) : "l"(src + (size_t)i * 4 * (NH * DH * 2)), "l"(policy_evict_first()) : "memory");
    }
    const int w = __shfl_sync(FULL, t >> 5, 0);
    const uint32_t sb = (uint32_t)__cvta_generic_to_shared(sm);
    const uint32_t bars = sb + SM_BAR;
    const int cq = c >> 4, cj = c & 15, c7 = c & 7;
    const int kg = c >> 5, ng = ((c >> 3) & 3) * 5 + c7;
    const bool is_wo = c7 < 5, is_f2 = c7 > 5 || cj == 5, is_f1 = !is_f2 && c7 >= 2 && !(cj == 13 && (cq & 3) == 2);
    const int fi = is_f2 ? cq * 5 + (cj < 8 ? cj - 5 : cj - 11) : cq * 7 - (cq > 2) - (cq > 6) + (cj < 8 ? cj - 2 : cj - 7);
    uint32_t* const A = P.arena;
    const size_t kv_off = ((size_t)h * SK + (SK - WIN)) * 256;

    if (w == 18) {
        const uint32_t tstart = gtime();
        uint32_t ep;
        uint32_t* po = A + a_o(0, h, r * 32 + perm16(lane)); PINL(po);
        {
            uint2 xs[5];
#pragma unroll
            for (int i = 0; i < 5; i++) xs[i] = __ldg((const uint2*)(P.x + lane * 4 + 128 * i));
            ep = ld_rlx1(A + A_EP);
            st_rlx1(po, 0u); st_rlx1(po + 1024, 0u);
            float s = 0.f;
#pragma unroll
            for (int i = 0; i < 5; i++) s += (bf_lo(xs[i].x) + bf_hi(xs[i].x)) + (bf_lo(xs[i].y) + bf_hi(xs[i].y));
#pragma unroll
            for (int m = 16; m; m >>= 1) s += shx(s, m);
            const float mean = s * (1.0f / D);
            float ss = 0.f;
#pragma unroll
            for (int i = 0; i < 5; i++) {
                float a = bf_lo(xs[i].x) - mean, b = bf_hi(xs[i].x) - mean, e = bf_lo(xs[i].y) - mean, f = bf_hi(xs[i].y) - mean;
                ss += (a * a + b * b) + (e * e + f * f);
            }
#pragma unroll
            for (int m = 16; m; m >>= 1) ss += shx(ss, m);
            const float mb = bfr(mean), rs = rcp_apx(bfr(sqrt_apx(bfr(bfr(ss * (1.0f / D)) + 1e-5f))));
#pragma unroll
            for (int i = 0; i < 5; i++) {
                const uint32_t d0 = pack2(bf_lo(xs[i].x) - mb, bf_hi(xs[i].x) - mb), d1 = pack2(bf_lo(xs[i].y) - mb, bf_hi(xs[i].y) - mb);
                *(uint2*)(sm + SM_XN + lane * 8 + i * 256) = make_uint2(pack2(bf_lo(d0) * rs, bf_hi(d0) * rs), pack2(bf_lo(d1) * rs, bf_hi(d1) * rs));
                *(uint2*)(sm + SM_X + lane * 8 + i * 256) = xs[i];
            }
            *(uint2*)(sm + SM_EP) = make_uint2(ep, 0u);
            bar_arrive(6, 544);
            TL(21);
        }
        const uint32_t tag = ep % 255u + 1u, e3 = ep % 3u + 1u, tag2 = ((e3 & 1u) << 15) | ((e3 & 2u) << 30);
        int side = 0;
        {
            uint32_t best[2] = {0xffffffffu, 0xffffffffu};
            if (lane == 0) { while ((int)(gtime() - tstart) < PROBE_T) __nanosleep(200); }
            __syncwarp();
#pragma unroll 1
            for (int i = 0; i < 2; i++) {
#pragma unroll
                for (int k = 0; k < 2; k++) {
                    uint32_t c0 = clk32(), c1, old = 0;
                    if (lane == 0) asm volatile("atom.relaxed.gpu.global.exch.b32 %0, [%1], 0;" : "=r"(old) : "l"(po + k * 1024) : "memory");
                    c1 = __any_sync(FULL, old != 0u) ? c0 : clk32();
                    best[k] = min(best[k], c1 - c0);
                }
            }
            side = __shfl_sync(FULL, best[1] < best[0], 0);
            ((volatile uint32_t*)(sm + SM_EP))[1] = side + 1;
            TL(22);
        }
        uint32_t row = sb + SM_RED + lane * 144; PIN(row);
        bar_sync(2, 544);
        { const uint32_t tv = pack2(0.f, rowsum32(row)) | tag; st_rlx1(po, tv); st_rlx1(po + 1024, tv); }
        TL(5);
        if (is_wo) {
            uint32_t* ph = A + a_hp(1, kg, ng * 32 + perm16(lane)); PINL(ph);
            bar_sync(3, 544);
            const uint32_t tv = tagw(rowsum32(row + (SM_PART2 - SM_RED)), tag);
            st_rlx1(ph, tv); st_rlx1(ph + 1024, tv);
            TL(8);
        }
        if (is_f1) {
            uint32_t* mbox = A + a_h1(lane & 1, fi >> 2, (fi & 3) * 16 + (perm16(lane) >> 1)); PINL(mbox);
            uint32_t sp = sb + SM_ST + (lane & 1) * 48, fp = sb + SM_FIN + lane * (FIN_PITCH * 4); PIN(sp); PIN(fp);
            bar_sync(4, 352);
            const float4 s0 = lds4(sp), s1 = lds4(sp + 16), s2 = lds4(sp + 32);
            const float4 a0 = lds4(fp), a1 = lds4(fp + 16), a2 = lds4(fp + 32), a3 = lds4(fp + 48), a4 = lds4(fp + 64), a5 = lds4(fp + 80);
            const float sa = (sum4(s0) + sum4(s1)) + (s2.x + s2.y), sb2 = shx(sa, 1);
            const float acc = (sum4(a0) + sum4(a1)) + (a2.x + a2.y), cs = (sum4(a3) + sum4(a4)) + (a5.x + a5.y);
            TLD(11, acc);
            const float mean = ((lane & 1) ? sa : sb2) * (1.0f / D);
            const float var = fmaxf(((lane & 1) ? sb2 : sa) * (1.0f / D) - mean * mean, 0.f);
            const float rs = rcp_apx(bfr(sqrt_apx(bfr(bfr(var) + 1e-5f))));
            const float hid = fmaxf((acc - bfr(mean) * cs) * rs, 0.f), oth = shx(hid, 1);
            st_rlx1(mbox, (((lane & 1) ? pack2(oth, hid) : pack2(hid, oth)) & 0x7fff7fffu) | tag2);
            TL(12);
        } else if (is_f2) {
            const int col = fi * 16 + (lane & 15);
            unsigned short* op = (unsigned short*)P.out + col; PINL(op);
            uint32_t fp = sb + SM_PART2 + (lane & 15) * 240 + (lane >> 4) * 112; PIN(fp);
            const float xv = __uint_as_float((uint32_t)((const unsigned short*)(sm + SM_X))[col] << 16);
            const uint32_t* p = A + a_hp(side, (lane >> 4) * 2, perm16(col));
            uint32_t u0, u1; int it = 0;
            mbar_wait(bars + 8 * (B_WO + 2));
            while (u0 = ld_rlx1(p), u1 = ld_rlx1(p + 4096), __any_sync(FULL, ((u0 ^ tag) | (u1 ^ tag)) & 0xffu) && ++it < SPIN_MAX) delay(200);
            float hs = untag(u0) + untag(u1);
            hs += shx(hs, 16);
            const float hval = bfr(xv + bfr(hs));
            bar_sync(5, 480);
            const float4 a0 = lds4(fp), a1 = lds4(fp + 16), a2 = lds4(fp + 32), a3 = lds4(fp + 48), a4 = lds4(fp + 64), a5 = lds4(fp + 80), a6 = lds4(fp + 96);
            float sum = ((sum4(a0) + sum4(a1)) + (sum4(a2) + sum4(a3))) + ((sum4(a4) + sum4(a5)) + sum4(a6));
            sum += shx(sum, 16);
            if (lane < 16) *op = (unsigned short)pack2(hval + bfr(sum), 0.f);
            if (fi == 0 && lane == 0) st_rlx1(A + A_EP, ep >= 764u ? 0u : ep + 1u);
            TL(16);
        }
        return;
    }
    if (w == 17) {
        const uint32_t t0 = gtime();
        volatile uint32_t* tab = (volatile uint32_t*)(sm + SM_TAB);
        tab[lane] = t0 + P.pf[lane]; if (lane < NSTEP - 32) tab[32 + lane] = t0 + P.pf[32 + lane];
        __syncwarp();
        if (lane == 0) {
#pragma unroll 1
            for (int i = 0; i < 32; i++) {
                wait_until(tab[i]);
                prefetch_l2((const char*)(i < 16 ? P.kc : P.vc) + (size_t)(i < 16 ? kv_pf_off<NGK>(i, c) : kv_pf_off<NGV>(i - 16, c)) * 4096, 4096);
            }
#pragma unroll 1
            for (int i = 0; i < 8; i++) { wait_until(tab[32 + i]); prefetch_l2((const char*)P.wo + c * 5120 + i * 655360, 5120); }
#pragma unroll 1
            for (int i = 0; i < 5; i++) { wait_until(tab[40 + i]); prefetch_l2((const char*)P.w1 + c * 3456 + i * 442368, 3456); }
#pragma unroll 1
            for (int i = 0; i < (c < 96 ? 7 : 6); i++) { wait_until(tab[45 + i]); prefetch_l2((const char*)P.w2 + c * 2560 + i * 327680, 2560); }
            TL(29);
        }
        return;
    }
    if (w == 16) {
        const uint32_t t0 = gtime();
        TL(0);
        if (lane == 0) {
            asm volatile("prefetch.tensormap [%0];" :: "l"(&map_v) : "memory");
            asm volatile("prefetch.tensormap [%0];" :: "l"(is_f2 ? &map_w2 : &map_wo) : "memory");
            asm volatile("prefetch.tensormap [%0];" :: "l"(&map_w1) : "memory");
#pragma unroll
            for (int i = 0; i < NBAR; i++) mbar_init(bars + 8 * i, 1);
            asm volatile("fence.mbarrier_init.release.cluster;" ::: "memory");
        }
        volatile uint32_t* tab = (volatile uint32_t*)(sm + SM_TAB + 256);
        tab[lane] = t0 + P.ld[lane]; if (lane < NSTEP - 32) tab[32 + lane] = t0 + P.ld[32 + lane];
        __syncwarp();
        bar_arrive(1, 544);
        if (lane == 0) {
#pragma unroll 1
            for (int i = 0; i < 8; i++) {
                wait_until(tab[kv_step<NGK>(i, h)] + kv_sub<NGK>(i));
                const int e = kv_box<NGK>(i, h);
                uint32_t b = bars + 8 * (B_K + e);
                mbar_expect_tx(b, 8192);
                bulk_g2s(sb + SM_K + e * 8192, (const char*)P.kc + kv_off + e * 32768 + r * 8192, 8192, b);
            }
#pragma unroll 1
            for (int i = 0; i < 8; i++) {
                wait_until(tab[16 + kv_step<NGV>(i, h)] + kv_sub<NGV>(i));
                const int e = kv_box<NGV>(i, h);
                uint32_t b = bars + 8 * (B_V + e);
                mbar_expect_tx(b, 8192);
                tma2d(sb + SM_V + e * 8192, &map_v, r * 32, h * SK + (SK - WIN) + e * 128, b);
            }
            if (is_wo) {
#pragma unroll 1
                for (int i = 0; i < 8; i++) {
                    wait_until(tab[32 + i]);
                    uint32_t b = bars + 8 * (B_WO + i);
                    mbar_expect_tx(b, 8192);
                    tma2d(sb + SM_WO + i * 8192, &map_wo, ng * 32, i * 512 + kg * 128, b);
                }
            }
            if (is_f1) {
                mbar_wait(bars + 8 * B_KFREE);
#pragma unroll 1
                for (int i = 0; i < 5; i++) {
                    wait_until(tab[40 + i]);
                    uint32_t b = bars + 8 * (B_W1 + i);
                    mbar_expect_tx(b, 8192);
                    tma2d(sb + SM_K + i * 8192, &map_w1, fi * 32, i * 128, b);
                }
            } else if (is_f2) {
#pragma unroll 1
                for (int i = 0; i < 7; i++) {
                    wait_until(tab[45 + i]);
                    uint32_t b = bars + 8 * (B_WO + i);
                    mbar_expect_tx(b, 8192);
                    tma2d(sb + SM_WO + i * 8192, &map_w2, fi * 16, i * 256, b);
                }
            }
            TL(30);
        }
        return;
    }

    float* red = (float*)(sm + SM_RED);
    float* mw = (float*)(sm + SM_MW);
    float* lw = (float*)(sm + SM_LW);
    const int g = lane >> 2, tq = lane & 3;
    const int selsh = (g & 1) << 4;

    {
        int o = -1;
        if (w < 4) o = A_QX + c * 128 + t;
        else if (w < 12) o = A_SX + h * WIN + (w - 4) * 128 + r * 32 + lane;
        else if (w < 14) { if (is_wo) o = a_hp(w - 12, kg, ng * 32 + lane); }
        else if (w == 14) { if (is_f1) o = a_h1(lane >> 4, fi >> 2, (fi & 3) * 16 + (lane & 15)); }
        if (o >= 0) st_rlx1(A + o, 0u);
    }
    uint32_t epoch, tag, tag2;
    {
        bar_sync(6, 544);
        uint32_t bs[5];
#pragma unroll
        for (int i = 0; i < 5; i++) bs[i] = (uint32_t)((const unsigned short*)(sm + SM_XN))[row0 + 4 * i] << selsh;
        if (w == 5) TLD(23, __uint_as_float(wv[0].x));
        if (w == 5) TLD(24, __uint_as_float(wv[4].x ^ wv[3].x ^ wv[2].x ^ wv[1].x));
        float d1[4] = {0.f, 0.f, 0.f, 0.f}, d2[4] = {0.f, 0.f, 0.f, 0.f};
        mma(d1, wv[0].x, wv[0].y, wv[1].x, wv[1].y, bs[0], bs[1]); mma(d2, wv[0].z, wv[0].w, wv[1].z, wv[1].w, bs[0], bs[1]);
        mma(d1, wv[2].x, wv[2].y, wv[3].x, wv[3].y, bs[2], bs[3]); mma(d2, wv[2].z, wv[2].w, wv[3].z, wv[3].w, bs[2], bs[3]);
        mma(d1, wv[4].x, wv[4].y, 0u, 0u, bs[4], 0u);              mma(d2, wv[4].z, wv[4].w, 0u, 0u, bs[4], 0u);
        if (tq < 2) *(float4*)(red + (w >> 1) * 128 + (w & 1) * 64 + g * 8 + tq * 4) =
            tq ? make_float4(d2[0], d2[1], d2[2], d2[3]) : make_float4(d1[0], d1[1], d1[2], d1[3]);
        bar_sync(1, 544);
        epoch = *(volatile uint32_t*)(sm + SM_EP);
        tag = epoch % 255u + 1u;
        { const uint32_t e3 = epoch % 3u + 1u; tag2 = ((e3 & 1u) << 15) | ((e3 & 2u) << 30); }
        if (w < 4) {
            float s2 = 0.f;
#pragma unroll
            for (int i = 0; i < 8; i++) s2 += red[i * 128 + t];
            if (w == 0) TLD(1, s2);
            st_rlx1(A + A_QX + c * 128 + t, tagw(s2, tag));
            const uint32_t* p = A + A_QX + h * 512 + t;
            uint4 v; int it = 0;
            do { v.x = ld_rlx1(p); v.y = ld_rlx1(p + 128); v.z = ld_rlx1(p + 256); v.w = ld_rlx1(p + 384); } while (__any_sync(FULL, bad4(v, tag)) && ++it < SPIN_MAX);
            ((unsigned short*)(sm + SM_QS))[t] = (unsigned short)pack2((untag(v.x) + untag(v.y)) + (untag(v.z) + untag(v.w)), 0.f);
        }
        bar_sync(1, 512);
    }

    int side;
    const bool tb0 = tq & 1, tb1 = tq & 2;
    uint32_t po = sb + SM_RED + (((tq >> 1) * 16 + g) * 36 + w * 2 + (tq & 1)) * 4;
    {
        const int ch0 = ((g & 1) * 4 + tq) * 16, ch1 = ch0 ^ 64;
        const uint4 q00 = *(const uint4*)(sm + SM_QS + ch0), q01 = *(const uint4*)(sm + SM_QS + ch1);
        const uint4 q10 = *(const uint4*)(sm + SM_QS + 128 + ch0), q11 = *(const uint4*)(sm + SM_QS + 128 + ch1);
        if (w == 0) TLD(2, __uint_as_float(q11.w));
        mbar_wait(bars + 8 * (B_K + (w >> 1)));
        if (w == 15) TL(3);
        const unsigned char* kp = sm + SM_K + (w * 16 + g) * 256;
        float sa[4] = {0.f, 0.f, 0.f, 0.f}, sb2[4] = {0.f, 0.f, 0.f, 0.f};
#define SCORE_STEP(off, Q) { const uint4 X = *(const uint4*)(kp + (off)), Y = *(const uint4*)(kp + 2048 + (off)); \
        mma(sa, X.x, Y.x, X.y, Y.y, Q.x, Q.y); mma(sb2, X.z, Y.z, X.w, Y.w, Q.z, Q.w); }
        SCORE_STEP(ch0, q00) SCORE_STEP(ch1, q01) SCORE_STEP(128 + ch0, q10) SCORE_STEP(128 + ch1, q11)
        float s0 = (g & 1) ? sa[1] + sb2[1] : sa[0] + sb2[0];
        float s1 = (g & 1) ? sa[3] + sb2[3] : sa[2] + sb2[2];
        s0 = bfr(bfr(s0) * 0.08838834764831845f);
        s1 = bfr(bfr(s1) * 0.08838834764831845f);
        if (tq < 2) st_rlx1(A + A_SX + h * WIN + (w >> 1) * 128 + r * 32 + (w & 1) * 16 + perm16(g + 8 * tq), __float_as_uint(tq ? s1 : s0) | tag);
        if (w == 15) TL(17);
        uint4 v;
        delay(SC_DELAY);
        { const uint32_t* p = A + A_SX + h * WIN + w * 64 + (lane & 15) * 4; int it = 0;
          while (v = ld_rlx4(p), __any_sync(FULL, bad4(v, tag)) && ++it < SPIN_MAX) delay(SC_BACKOFF); }
        float e0 = bf_hi(v.x), e1 = bf_hi(v.y), e2 = bf_hi(v.z), e3 = bf_hi(v.w);
        float m = fmaxf(fmaxf(e0, e1), fmaxf(e2, e3));
        m = fmaxf(m, shx(m, 1)); m = fmaxf(m, shx(m, 2)); m = fmaxf(m, shx(m, 4)); m = fmaxf(m, shx(m, 8));
        if (lane == 0) mw[w] = m;
        bar_sync(1, 512);
        if (t == 0) mbar_arrive(bars + 8 * B_KFREE);
        float M = mw[lane & 15];
        M = fmaxf(M, shx(M, 1)); M = fmaxf(M, shx(M, 2)); M = fmaxf(M, shx(M, 4)); M = fmaxf(M, shx(M, 8));
        e0 = ex2((e0 - M) * LOG2E); e1 = ex2((e1 - M) * LOG2E); e2 = ex2((e2 - M) * LOG2E); e3 = ex2((e3 - M) * LOG2E);
        float l = (e0 + e1) + (e2 + e3);
        l += shx(l, 1); l += shx(l, 2); l += shx(l, 4); l += shx(l, 8);
        if (lane == 0) lw[w] = l;
        bar_sync(1, 512);
        float L = lw[lane & 15];
        L += shx(L, 1); L += shx(L, 2); L += shx(L, 4); L += shx(L, 8);
        L = rcp_apx(L);
        const uint32_t b0 = pack2(e0 * L, e1 * L), b1 = pack2(e2 * L, e3 * L);
        if (w == 15) TLD(19, __uint_as_float(b0));
        mbar_wait(bars + 8 * (B_V + (w >> 1)));
        if (w == 15) TL(4);
        uint32_t af[8][4]; float e[8][4];
        frags<true>(af, sb + SM_V + w * 4096, lane); zero8(e); mma8(e, af, b0, b1); store_part(e, po, tb0, tb1);
        bar_arrive(2, 544);
    }
    po += SM_PART2 - SM_RED; PIN(po);
    { int it = 0; while ((side = ((volatile uint32_t*)(sm + SM_EP))[1]) == 0 && ++it < SPIN_MAX) {} side = __shfl_sync(FULL, side, 0) > 1; }

    if (is_wo) {
        const uint32_t* p = A + a_o(side, kg, w * 64 + (lane & 15) * 4);
        uint4 va; uint32_t b0, b1;
        uint32_t af[8][4]; float e[8][4];
        mbar_wait(bars + 8 * (B_WO + (w >> 2)));
        poll1<true>(va, [&](uint4& v) { v = ld_rlx4(p); },
              [&](const uint4& v) { b0 = __byte_perm(v.x, v.y, 0x7632); b1 = __byte_perm(v.z, v.w, 0x7632); return bad4(v, tag); },
              af, sb + SM_WO + w * 4096, bars + 8 * (B_WO + (w >> 1)), lane);
        if (w == 15) TL(7);
        zero8(e); mma8(e, af, b0, b1); store_part(e, po, tb0, tb1);
        bar_arrive(3, 544);
    }

    if (is_f1) {
        if (w < 10) {
            const uint32_t* xp = (const uint32_t*)(sm + SM_X) + w * 32 + (g & 3) * 8 + tq;
            const float x0 = bf_lo(xp[0]), x1 = bf_hi(xp[0]), x2 = bf_lo(xp[4]), x3 = bf_hi(xp[4]);
            uint32_t fo = sb + SM_FIN + ((16 * (tq & 1) + g) * FIN_PITCH + (tq >> 1) * 12 + w) * 4; PIN(fo);
            uint32_t so = sb + SM_ST + ((lane >> 1) * 12 + w) * 4; PIN(so);
            const bool stv = g < 4 && (tq & 1) == (g >> 1);
            const uint32_t* p = A + a_hp(side, (lane >> 4) * 2, w * 64 + (lane & 15) * 4);
            mbar_wait(bars + 8 * B_W1);
            uint32_t af[8][4], b0, b1;
            Set2 va;
            poll1<true>(va, [&](Set2& v) { v.a = ld_rlx4(p); v.b = ld_rlx4(p + 4096); },
                  [&](const Set2& v) {
                      const uint32_t y0 = v.a.x ^ tag, y1 = v.a.y ^ tag, y2 = v.a.z ^ tag, y3 = v.a.w ^ tag, z0 = v.b.x ^ tag, z1 = v.b.y ^ tag, z2 = v.b.z ^ tag, z3 = v.b.w ^ tag;
                      float s0 = __uint_as_float(y0) + __uint_as_float(z0), s1 = __uint_as_float(y1) + __uint_as_float(z1);
                      float s2 = __uint_as_float(y2) + __uint_as_float(z2), s3 = __uint_as_float(y3) + __uint_as_float(z3);
                      s0 += shx(s0, 16); s1 += shx(s1, 16); s2 += shx(s2, 16); s3 += shx(s3, 16);
                      b0 = pack2(x0 + bfr(s0), x1 + bfr(s1)); b1 = pack2(x2 + bfr(s2), x3 + bfr(s3));
                      if (g >= 4) { b0 = 0x3f803f80u; b1 = 0x3f803f80u; }
                      return ((y0 | y1 | y2) | (y3 | z0 | z1) | (z2 | z3)) & 0xffu;
                  },
                  af, sb + SM_K + w * 4096, bars + 8 * (B_W1 + (w >> 1)), lane);
            if (w == 9) TL(10);
            float e[8][4], gm[4] = {0.f, 0.f, 0.f, 0.f};
            mma(gm, b0, 0u, b1, 0u, b0, b1);
            zero8(e); mma8(e, af, b0, b1);
            float st = stv ? ((g & 1) ? gm[1] : gm[0]) : 0.f;
            st += shx(st, 4);
            const float l0 = tb0 ? e[2][0] + e[3][1] : e[0][0] + e[1][1], h0 = tb0 ? e[2][2] + e[3][3] : e[0][2] + e[1][3];
            const float l1 = tb0 ? e[6][0] + e[7][1] : e[4][0] + e[5][1], h1 = tb0 ? e[6][2] + e[7][3] : e[4][2] + e[5][3];
            st += shx(st, 9);
            sts(fo, (tb0 ? l1 : l0) + shx(tb0 ? l0 : l1, 1));
            sts(fo + 8 * FIN_PITCH * 4, (tb0 ? h1 : h0) + shx(tb0 ? h0 : h1, 1));
            if (!(lane & 29)) sts(so, st);
            bar_arrive(4, 352);
        }
    } else if (is_f2) {
        if (w < 14) {
            const bool live = w < 13 || lane < 16;
            const uint32_t* p = A + a_h1(side, w, (live ? lane : lane - 16) * 2);
            const uint32_t msk = live ? 0x7fff7fffu : 0u;
            uint32_t qo = sb + SM_PART2 + (g * 60 + w * 4 + tq) * 4; PIN(qo);
            mbar_wait(bars + 8 * (B_WO + 3));
            uint32_t af[8][4]; uint2 v;
            poll1<false>(v, [&](uint2& u) { u = ld_rlx2(p); }, [&](const uint2& u) { return ((u.x ^ tag2) | (u.y ^ tag2)) & 0x80008000u; },
                         af, sb + SM_WO + w * 4096, bars + 8 * (B_WO + (w >> 1)), lane);
            if (w == 0) TL(14);
            float e[8][4];
            zero8(e);
            mma8(e, af, v.x & msk, v.y & msk);
            const float l0 = tb0 ? e[2][0] + e[3][1] : e[0][0] + e[1][1], h0 = tb0 ? e[2][2] + e[3][3] : e[0][2] + e[1][3];
            const float l1 = tb0 ? e[6][0] + e[7][1] : e[4][0] + e[5][1], h1 = tb0 ? e[6][2] + e[7][3] : e[4][2] + e[5][3];
            sts(qo, tb1 ? l1 : l0); sts(qo + 8 * 240, tb1 ? h1 : h0);
            bar_arrive(5, 480);
        }
    }
}

typedef CUresult (*EncodeFn)(CUtensorMap*, CUtensorMapDataType, cuuint32_t, void*, const cuuint64_t*, const cuuint64_t*,
                             const cuuint32_t*, const cuuint32_t*, CUtensorMapInterleave, CUtensorMapSwizzle,
                             CUtensorMapL2promotion, CUtensorMapFloatOOBfill);
float g_par[11] = {1200.f, 164.f, 164.f, 400.f, 164.f, 0.f, 250.f, 500.f, 500.f, 200.f, 100.f};

void make_map(EncodeFn enc, CUtensorMap* m, void* base, int cols, int rows, int bc, int br, CUtensorMapSwizzle sw = CU_TENSOR_MAP_SWIZZLE_64B) {
    cuuint64_t gd[2] = {(cuuint64_t)cols, (cuuint64_t)rows}; cuuint64_t gs[1] = {(cuuint64_t)cols * 2};
    cuuint32_t bd[2] = {(cuuint32_t)bc, (cuuint32_t)br}; cuuint32_t es[2] = {1, 1};
    enc(m, CU_TENSOR_MAP_DATA_TYPE_BFLOAT16, 2, base, gd, gs, bd, es, CU_TENSOR_MAP_INTERLEAVE_NONE, sw,
        CU_TENSOR_MAP_L2_PROMOTION_L2_128B, CU_TENSOR_MAP_FLOAT_OOB_FILL_NONE);
}

}

extern "C" void kernel_launch(void* const* d_in, const int* in_sizes, int n_in, void* d_out, int out_size) {
    (void)in_sizes; (void)n_in; (void)out_size;
    static EncodeFn enc = nullptr;
    static uint32_t* arena = nullptr;
    if (!enc) {
        void* sym = nullptr;
        cudaGetSymbolAddress(&sym, g_arena);
        arena = (uint32_t*)(((uintptr_t)sym + 65535) & ~(uintptr_t)65535);
        cudaDriverEntryPointQueryResult qr;
        cudaGetDriverEntryPoint("cuTensorMapEncodeTiled", (void**)&enc, cudaEnableDefault, &qr);
        cudaFuncSetAttribute(fused_decode_kernel, cudaFuncAttributeMaxDynamicSharedMemorySize, SM_TOTAL);
    }
    CUtensorMap mv, mwo, mw1, mw2;
    make_map(enc, &mv, d_in[2], DH, NH * SK, 32, 128);
    make_map(enc, &mwo, d_in[4], D, NH * DH, 32, 128);
    make_map(enc, &mw1, d_in[6], DFF, D, 32, 128);
    make_map(enc, &mw2, d_in[7], D, DFF, 16, 256, CU_TENSOR_MAP_SWIZZLE_32B);
    Params P = {(const __nv_bfloat16*)d_in[0], (const __nv_bfloat16*)d_in[1], (const __nv_bfloat16*)d_in[2], (const __nv_bfloat16*)d_in[3],
                (const __nv_bfloat16*)d_in[4], (const __nv_bfloat16*)d_in[6], (const __nv_bfloat16*)d_in[7], (__nv_bfloat16*)d_out, arena};
    float t = g_par[0];
    for (int i = 0; i < NSTEP; i++) {
        if (i == 40) t += g_par[3];
        if (i == 45) t += g_par[5];
        P.pf[i] = (uint32_t)t;
        P.ld[i] = (uint32_t)(t + g_par[i < 32 ? 7 : i < 40 ? 8 : i < 45 ? 9 : 10]);
        t += i < 32 ? g_par[1] : i < 40 ? 1.25f * g_par[2] : i < 45 ? 0.84375f * g_par[4] : 0.625f * g_par[6];
    }
    fused_decode_kernel<<<NCTA, NTHREADS, SM_TOTAL, cudaStreamPerThread>>>(P, mv, mwo, mw1, mw2);
}
```

```cpp
#include <cuda_runtime.h>
#include <cuda_bf16.h>
#include <cuda.h>
#include <stdint.h>

namespace {

constexpr int D = 640, DH = 128, NH = 32, SK = 4096, WIN = 1024, DFF = 1728;
constexpr int NCTA = 128;
constexpr int NTHREADS = 608;

constexpr int SC_BACKOFF = 100;

constexpr int FIN_PITCH = 28;
constexpr int SM_K = 0;
constexpr int SM_V = 65536;
constexpr int SM_WO = 131072;
constexpr int SM_RED = SM_WO + 65536;
constexpr int SM_PART2 = SM_RED + 32 * 36 * 4;
constexpr int SM_FIN = SM_PART2 + 32 * 36 * 4;
constexpr int SM_ST = SM_FIN + 32 * FIN_PITCH * 4;
constexpr int SM_QS = SM_ST + 96;
constexpr int SM_X = SM_QS + 256;
constexpr int SM_XN = SM_X + 1280;
constexpr int SM_MW = SM_XN + 1280;
constexpr int SM_LW = SM_MW + 64;
constexpr int SM_RT = SM_LW + 64;
constexpr int SM_BAR = SM_RT + 64;
constexpr int SM_EP = SM_BAR + 256;
constexpr int SM_TAB = SM_EP + 32;
constexpr int SM_TOTAL = SM_TAB + 512;

constexpr int B_K = 0, B_V = 8, B_WO = 16, B_W1 = 24, B_KFREE = 29, NBAR = 30;
constexpr int NSTEP = 52;
constexpr int SPIN_MAX = 1 << 20;
constexpr unsigned FULL = 0xffffffffu;
constexpr float LOG2E = 1.4426950408889634f;

constexpr int A_QX = 16384;
constexpr int A_SX = A_QX + NCTA * 128;
constexpr int A_EP = A_SX + NH * WIN;
constexpr int A_WORDS = A_EP + 32;
__device__ uint32_t g_arena[A_WORDS + 131072];
__device__ __forceinline__ int a_sx(int head, int key) { return A_SX + (head >> 1) * 2048 + (key >> 9) * 1024 + (head & 1) * 512 + (key & 511); }
__device__ __forceinline__ int a_o(int s, int head, int i) { return (head & 3) * 4096 + s * 1024 + (head >> 2) * 128 + i; }
__device__ __forceinline__ int a_hp(int s, int k, int i) { return k * 4096 + (3 - s) * 1024 + i; }
__device__ __forceinline__ int a_h1(int s, int tile, int i) { return (tile >> 2) * 4096 + (3 - s) * 1024 + D + (tile & 3) * 64 + i; }

__device__ __forceinline__ uint32_t gtime() { uint32_t t; asm volatile("mov.u32 %0, %%globaltimer_lo;" : "=r"(t) :: "memory"); return t; }
__device__ __forceinline__ uint32_t clk32() { uint32_t t; asm volatile("mov.u32 %0, %%clock;" : "=r"(t) :: "memory"); return t; }
__device__ __forceinline__ uint32_t pack2(float lo, float hi) { uint32_t d; asm("cvt.rn.bf16x2.f32 %0, %1, %2;" : "=r"(d) : "f"(hi), "f"(lo)); return d; }
__device__ __forceinline__ float bfr(float x) { return __uint_as_float(pack2(0.f, x)); }
__device__ __forceinline__ float bf_lo(uint32_t w) { return __uint_as_float(w << 16); }
__device__ __forceinline__ float bf_hi(uint32_t w) { return __uint_as_float(w & 0xffff0000u); }
__device__ __forceinline__ uint32_t tagw(float v, uint32_t tag) { return (__float_as_uint(v) & 0xfffffffcu) | tag; }
__device__ __forceinline__ float untag(uint32_t w) { return __uint_as_float(w & 0xfffffffcu); }
__device__ __forceinline__ uint32_t bad4(const uint4& v, uint32_t tag) { return ((v.x ^ tag) | (v.y ^ tag) | (v.z ^ tag) | (v.w ^ tag)) & 3u; }
__device__ __forceinline__ int perm16(int i) { return (i & ~15) | ((i & 6) << 1) | ((i & 8) >> 2) | (i & 1); }

__device__ __forceinline__ void mbar_init(uint32_t bar, uint32_t cnt) { asm volatile("mbarrier.init.shared::cta.b64 [%0], %1;" :: "r"(bar), "r"(cnt) : "memory"); }
__device__ __forceinline__ void mbar_expect_tx(uint32_t bar, uint32_t bytes) { asm volatile("mbarrier.arrive.expect_tx.shared::cta.b64 _, [%0], %1;" :: "r"(bar), "r"(bytes) : "memory"); }
__device__ __forceinline__ void mbar_arrive(uint32_t bar) { asm volatile("mbarrier.arrive.shared::cta.b64 _, [%0];" :: "r"(bar) : "memory"); }
__device__ __forceinline__ void mbar_wait(uint32_t bar) {
    uint32_t done; int it = 0;
    do {
        asm volatile("{\n.reg .pred p;\nmbarrier.try_wait.parity.shared::cta.b64 p, [%1], 0, 20000;\nselp.u32 %0, 1, 0, p;\n}" : "=r"(done) : "r"(bar) : "memory");
    } while (!done && ++it < SPIN_MAX);
}
__device__ __forceinline__ bool mbar_test(uint32_t bar) {
    uint32_t done;
    asm volatile("{\n.reg .pred p;\nmbarrier.test_wait.parity.shared::cta.b64 p, [%1], 0;\nselp.u32 %0, 1, 0, p;\n}" : "=r"(done) : "r"(bar) : "memory");
    return __all_sync(0xffffffffu, done);
}
__device__ __forceinline__ uint64_t policy_evict_first() { uint64_t p; asm("createpolicy.fractional.L2::evict_first.b64 %0, 1.0;" : "=l"(p)); return p; }
__device__ __forceinline__ void bulk_g2s(uint32_t dst, const void* src, uint32_t bytes, uint32_t bar) {
    asm volatile("cp.async.bulk.shared::cluster.global.mbarrier::complete_tx::bytes [%0], [%1], %2, [%3];" :: "r"(dst), "l"(src), "r"(bytes), "r"(bar) : "memory");
}
__device__ __forceinline__ void tma2d(uint32_t dst, const CUtensorMap* m, int c0, int c1, uint32_t bar) {
    asm volatile("cp.async.bulk.tensor.2d.shared::cluster.global.mbarrier::complete_tx::bytes [%0], [%1, {%3, %4}], [%2];" :: "r"(dst), "l"(m), "r"(bar), "r"(c0), "r"(c1) : "memory");
}
__device__ __forceinline__ void prefetch_l2(const void* src, uint32_t bytes) {
    asm volatile("cp.async.bulk.prefetch.L2.global.L2::cache_hint [%0], %1, %2;" :: "l"(src), "r"(bytes), "l"(policy_evict_first()) : "memory");
}
__device__ __forceinline__ void wait_until(uint32_t tgt) {
    int it = 0;
    while ((int)(gtime() - tgt) < 0 && ++it < SPIN_MAX) {}
}
__device__ __forceinline__ void bar_sync(int id, int n) { asm volatile("bar.sync %0, %1;" :: "r"(id), "r"(n) : "memory"); }
__device__ __forceinline__ void bar_arrive(int id, int n) { asm volatile("bar.arrive %0, %1;" :: "r"(id), "r"(n) : "memory"); }
__device__ __forceinline__ uint4 ld_rlx4(const void* p) {
    uint4 v; asm volatile("ld.relaxed.gpu.global.v4.u32 {%0,%1,%2,%3}, [%4];" : "=r"(v.x), "=r"(v.y), "=r"(v.z), "=r"(v.w) : "l"(p) : "memory"); return v;
}
__device__ __forceinline__ uint2 ld_rlx2(const void* p) {
    uint2 v; asm volatile("ld.relaxed.gpu.global.v2.u32 {%0,%1}, [%2];" : "=r"(v.x), "=r"(v.y) : "l"(p) : "memory"); return v;
}
__device__ __forceinline__ uint32_t ld_rlx1(const void* p) {
    uint32_t v; asm volatile("ld.relaxed.gpu.global.u32 %0, [%1];" : "=r"(v) : "l"(p) : "memory"); return v;
}
__device__ __forceinline__ void st_rlx1(void* p, uint32_t v) { asm volatile("st.relaxed.gpu.global.u32 [%0], %1;" :: "l"(p), "r"(v) : "memory"); }
__device__ __forceinline__ float sqrt_apx(float x) { float y; asm("sqrt.approx.f32 %0, %1;" : "=f"(y) : "f"(x)); return y; }
__device__ __forceinline__ float ex2(float x) { float y; asm("ex2.approx.ftz.f32 %0, %1;" : "=f"(y) : "f"(x)); return y; }
__device__ __forceinline__ float rcp_apx(float x) { float y; asm("rcp.approx.ftz.f32 %0, %1;" : "=f"(y) : "f"(x)); return y; }
__device__ __forceinline__ float shx(float v, int m) { return __shfl_xor_sync(FULL, v, m); }
__device__ __forceinline__ void delay(uint32_t n) { uint32_t t0 = clk32(); while (clk32() - t0 < n) {} }
__device__ __forceinline__ float sum4(const float4& a) { return (a.x + a.y) + (a.z + a.w); }

__device__ __forceinline__ void mma(float* d, uint32_t a0, uint32_t a1, uint32_t a2, uint32_t a3, uint32_t b0, uint32_t b1) {
    asm("mma.sync.aligned.m16n8k16.row.col.f32.bf16.bf16.f32 {%0,%1,%2,%3}, {%4,%5,%6,%7}, {%8,%9}, {%0,%1,%2,%3};"
        : "+f"(d[0]), "+f"(d[1]), "+f"(d[2]), "+f"(d[3]) : "r"(a0), "r"(a1), "r"(a2), "r"(a3), "r"(b0), "r"(b1));
}
__device__ __forceinline__ void ldsm4t(uint32_t* r, uint32_t addr) {
    asm volatile("ldmatrix.sync.aligned.m8n8.x4.trans.shared.b16 {%0,%1,%2,%3}, [%4];" : "=r"(r[0]), "=r"(r[1]), "=r"(r[2]), "=r"(r[3]) : "r"(addr) : "memory");
}
template <bool W64>
__device__ __forceinline__ void frags(uint32_t (*af)[4], uint32_t tile, int lane) {
    const int row = (lane & 7) + 8 * (lane >> 4);
    if (W64) {
        const uint32_t ad = tile + row * 64 + ((((lane >> 3) & 1) ^ ((lane >> 1) & 3)) << 4);
#pragma unroll
        for (int j = 0; j < 8; j++) ldsm4t(af[j], (ad ^ ((j >> 2) << 5)) + (j & 3) * 1024);
    } else {
        const uint32_t ad = tile + row * 32 + ((((lane >> 3) ^ (lane >> 2)) & 1) << 4);
#pragma unroll
        for (int j = 0; j < 8; j++) ldsm4t(af[j], ad + j * 512);
    }
}
__device__ __forceinline__ void mma8(float (*e)[4], const uint32_t (*af)[4], uint32_t b0, uint32_t b1) {
#pragma unroll
    for (int j = 0; j < 8; j++) mma(e[j], af[j][0], af[j][1], af[j][2], af[j][3], b0, b1);
}
__device__ __forceinline__ void zero8(float (*e)[4]) {
#pragma unroll
    for (int j = 0; j < 8; j++) { e[j][0] = 0.f; e[j][1] = 0.f; e[j][2] = 0.f; e[j][3] = 0.f; }
}
#define PIN(x) asm volatile("" : "+r"(x))
#define PINL(x) asm volatile("" : "+l"(x))
__device__ __forceinline__ void sts(uint32_t addr, float v) { asm volatile("st.shared.f32 [%0], %1;" :: "r"(addr), "f"(v) : "memory"); }
__device__ __forceinline__ float4 lds4(uint32_t addr) {
    float4 v; asm volatile("ld.shared.v4.f32 {%0,%1,%2,%3}, [%4];" : "=f"(v.x), "=f"(v.y), "=f"(v.z), "=f"(v.w) : "r"(addr) : "memory"); return v;
}
__device__ __forceinline__ void store_part(float (*e)[4], uint32_t po, bool t0, bool t1) {
    const float l0 = t0 ? e[2][0] + e[3][1] : e[0][0] + e[1][1], h0 = t0 ? e[2][2] + e[3][3] : e[0][2] + e[1][3];
    const float l1 = t0 ? e[6][0] + e[7][1] : e[4][0] + e[5][1], h1 = t0 ? e[6][2] + e[7][3] : e[4][2] + e[5][3];
    sts(po, t1 ? l1 : l0); sts(po + 8 * 36 * 4, t1 ? h1 : h0);
}
__device__ __forceinline__ float rowsum32(uint32_t row) {
    const float4 a = lds4(row), b = lds4(row + 16), c = lds4(row + 32), d = lds4(row + 48), e = lds4(row + 64), f = lds4(row + 80), g = lds4(row + 96), h = lds4(row + 112);
    return ((sum4(a) + sum4(b)) + (sum4(c) + sum4(d))) + ((sum4(e) + sum4(f)) + (sum4(g) + sum4(h)));
}
template <bool W64, class Set, class Issue, class Proc>
__device__ __forceinline__ void poll1(Set& sa, Issue issue, Proc proc, uint32_t (*af)[4], uint32_t tile, uint32_t bar, int lane) {
    bool have = false, bad = true;
#pragma unroll 1
    for (int it = 0; it < SPIN_MAX; it++) {
        if (bad) issue(sa);
        if (!have) { have = mbar_test(bar); if (have) frags<W64>(af, tile, lane); }
        if (bad) bad = __any_sync(FULL, proc(sa));
        if (have && !bad) break;
    }
}
__device__ __forceinline__ int near_copy(const unsigned char* sm, int h, int lane) {
    uint32_t v = ((const uint32_t*)(sm + SM_RT))[lane & 15];
    v = min(v, __shfl_xor_sync(FULL, v, 1)); v = min(v, __shfl_xor_sync(FULL, v, 2)); v = min(v, __shfl_xor_sync(FULL, v, 4));
    const int second = __shfl_sync(FULL, v, 8) < __shfl_sync(FULL, v, 0);
    return (__popc((uint32_t)a_sx(h, 0) * 4u & 0xb3000u) & 1) ^ second;
}
struct Set2 { uint4 a, b; };

struct Params {
    const __nv_bfloat16 *x, *kc, *vc, *wq, *wo, *w1, *w2;
    __nv_bfloat16* out;
    uint32_t* arena;
    uint32_t pf[NSTEP], ld[NSTEP];
};

__global__ void __launch_bounds__(NTHREADS, 1)
fused_decode_kernel(const __grid_constant__ Params P, const __grid_constant__ CUtensorMap map_v, const __grid_constant__ CUtensorMap map_wo,
                    const __grid_constant__ CUtensorMap map_w1, const __grid_constant__ CUtensorMap map_w2)
{
    extern __shared__ __align__(1024) unsigned char sm[];
    const int t = threadIdx.x, lane = t & 31;
    const int c = blockIdx.x, h = c >> 2, r = c & 3;
    uint4 wv[5];
    const int row0 = r * 160 + (t >> 6) * 20 + (t & 3);
    if (t < 512) {
        const char* src = (const char*)P.wq + (size_t)row0 * (NH * DH * 2) + h * 256 + (t & 60) * 4;
#pragma unroll
        for (int i = 0; i < 5; i++)
            asm volatile("ld.global.nc.L1::no_allocate.L2::cache_hint.v4.u32 {%0,%1,%2,%3}, [%4], %5;" : "=r"(wv[i].x), "=r"(wv[i].y), "=r"(wv[i].z), "=r"(wv[i].w) : "l"(src + (size_t)i * 4 * (NH * DH * 2)), "l"(policy_evict_first()) : "memory");
    }
    const int w = __shfl_sync(FULL, t >> 5, 0);
    const uint32_t sb = (uint32_t)__cvta_generic_to_shared(sm);
    const uint32_t bars = sb + SM_BAR;
    const int cq = c >> 4, cj = c & 15, c7 = c & 7;
    const int kg = c >> 5, ng = ((c >> 3) & 3) * 5 + c7;
    const bool is_wo = c7 < 5, is_f2 = c7 > 5 || cj == 5, is_f1 = !is_f2 && c7 >= 2 && !(cj == 13 && (cq & 3) == 2);
    const int fi = is_f2 ? cq * 5 + (cj < 8 ? cj - 5 : cj - 11) : cq * 7 - (cq > 2) - (cq > 6) + (cj < 8 ? cj - 2 : cj - 7);
    uint32_t* const A = P.arena;
    const size_t kv_off = ((size_t)h * SK + (SK - WIN)) * 256;

    if (w == 18) {
        uint32_t ep;
        uint32_t* po = A + a_o(0, h, r * 32 + perm16(lane)); PINL(po);
        {
            uint2 xs[5];
#pragma unroll
            for (int i = 0; i < 5; i++) xs[i] = __ldg((const uint2*)(P.x + lane * 4 + 128 * i));
            ep = ld_rlx1(A + A_EP);
            st_rlx1(po, 0u); st_rlx1(po + 1024, 0u);
            float s = 0.f;
#pragma unroll
            for (int i = 0; i < 5; i++) s += (bf_lo(xs[i].x) + bf_hi(xs[i].x)) + (bf_lo(xs[i].y) + bf_hi(xs[i].y));
#pragma unroll
            for (int m = 16; m; m >>= 1) s += shx(s, m);
            const float mean = s * (1.0f / D);
            float ss = 0.f;
#pragma unroll
            for (int i = 0; i < 5; i++) {
                float a = bf_lo(xs[i].x) - mean, b = bf_hi(xs[i].x) - mean, e = bf_lo(xs[i].y) - mean, f = bf_hi(xs[i].y) - mean;
                ss += (a * a + b * b) + (e * e + f * f);
            }
#pragma unroll
            for (int m = 16; m; m >>= 1) ss += shx(ss, m);
            const float mb = bfr(mean), rs = rcp_apx(bfr(sqrt_apx(bfr(bfr(ss * (1.0f / D)) + 1e-5f))));
#pragma unroll
            for (int i = 0; i < 5; i++) {
                const uint32_t d0 = pack2(bf_lo(xs[i].x) - mb, bf_hi(xs[i].x) - mb), d1 = pack2(bf_lo(xs[i].y) - mb, bf_hi(xs[i].y) - mb);
                *(uint2*)(sm + SM_XN + lane * 8 + i * 256) = make_uint2(pack2(bf_lo(d0) * rs, bf_hi(d0) * rs), pack2(bf_lo(d1) * rs, bf_hi(d1) * rs));
                *(uint2*)(sm + SM_X + lane * 8 + i * 256) = xs[i];
            }
            *(uint32_t*)(sm + SM_EP) = ep;
            bar_arrive(6, 544);
        }
        const uint32_t tag = ep + 1u, tag2 = ((tag & 1u) << 15) | ((tag & 2u) << 30);
        uint32_t row = sb + SM_RED + lane * 144; PIN(row);
        bar_sync(2, 544);
        { const uint32_t tv = pack2(0.f, rowsum32(row)) | tag; st_rlx1(po, tv); st_rlx1(po + 1024, tv); }
        if (is_wo) {
            uint32_t* ph = A + a_hp(1, kg, ng * 32 + perm16(lane)); PINL(ph);
            bar_sync(3, 544);
            const uint32_t tv = tagw(rowsum32(row + (SM_PART2 - SM_RED)), tag);
            st_rlx1(ph, tv); st_rlx1(ph + 1024, tv);
        }
        if (is_f1) {
            uint32_t* mbox = A + a_h1(lane & 1, fi >> 2, (fi & 3) * 16 + (perm16(lane) >> 1)); PINL(mbox);
            uint32_t sp = sb + SM_ST + (lane & 1) * 48, fp = sb + SM_FIN + lane * (FIN_PITCH * 4); PIN(sp); PIN(fp);
            bar_sync(4, 352);
            const float4 s0 = lds4(sp), s1 = lds4(sp + 16), s2 = lds4(sp + 32);
            const float4 a0 = lds4(fp), a1 = lds4(fp + 16), a2 = lds4(fp + 32), a3 = lds4(fp + 48), a4 = lds4(fp + 64), a5 = lds4(fp + 80);
            const float sa = (sum4(s0) + sum4(s1)) + (s2.x + s2.y), sb2 = shx(sa, 1);
            const float acc = (sum4(a0) + sum4(a1)) + (a2.x + a2.y), cs = (sum4(a3) + sum4(a4)) + (a5.x + a5.y);
            const float mean = ((lane & 1) ? sa : sb2) * (1.0f / D);
            const float var = fmaxf(((lane & 1) ? sb2 : sa) * (1.0f / D) - mean * mean, 0.f);
            const float rs = rcp_apx(bfr(sqrt_apx(bfr(bfr(var) + 1e-5f))));
            const float hid = fmaxf((acc - bfr(mean) * cs) * rs, 0.f), oth = shx(hid, 1);
            st_rlx1(mbox, (((lane & 1) ? pack2(oth, hid) : pack2(hid, oth)) & 0x7fff7fffu) | tag2);
        } else if (is_f2) {
            const int col = fi * 16 + (lane & 15);
            unsigned short* op = (unsigned short*)P.out + col; PINL(op);
            uint32_t fp = sb + SM_PART2 + (lane & 15) * 240 + (lane >> 4) * 112; PIN(fp);
            const float xv = __uint_as_float((uint32_t)((const unsigned short*)(sm + SM_X))[col] << 16);
            const uint32_t* p = A + a_hp(near_copy(sm, h, lane), (lane >> 4) * 2, perm16(col));
            uint32_t u0, u1; int it = 0;
            mbar_wait(bars + 8 * (B_WO + 2));
            while (u0 = ld_rlx1(p), u1 = ld_rlx1(p + 4096), __any_sync(FULL, ((u0 ^ tag) | (u1 ^ tag)) & 3u) && ++it < SPIN_MAX) delay(200);
            float hs = untag(u0) + untag(u1);
            hs += shx(hs, 16);
            const float hval = bfr(xv + bfr(hs));
            bar_sync(5, 480);
            const float4 a0 = lds4(fp), a1 = lds4(fp + 16), a2 = lds4(fp + 32), a3 = lds4(fp + 48), a4 = lds4(fp + 64), a5 = lds4(fp + 80), a6 = lds4(fp + 96);
            float sum = ((sum4(a0) + sum4(a1)) + (sum4(a2) + sum4(a3))) + ((sum4(a4) + sum4(a5)) + sum4(a6));
            sum += shx(sum, 16);
            if (lane < 16) *op = (unsigned short)pack2(hval + bfr(sum), 0.f);
            if (fi == 0 && lane == 0) st_rlx1(A + A_EP, ep >= 2u ? 0u : ep + 1u);
        }
        return;
    }
    if (w == 17) {
        const uint32_t t0 = gtime();
        volatile uint32_t* tab = (volatile uint32_t*)(sm + SM_TAB);
        tab[lane] = t0 + P.pf[lane]; if (lane < NSTEP - 32) tab[32 + lane] = t0 + P.pf[32 + lane];
        __syncwarp();
        if (lane == 0) {
#pragma unroll 1
            for (int i = 0; i < 32; i++) {
                wait_until(tab[i]);
                prefetch_l2((const char*)(i < 16 ? P.kc : P.vc) + (size_t)((cq * 4 + ((i >> 3) & 1) * 2 + ((c >> 3) & 1)) * 32 + 24 + ((i + (c >> 3)) & 7)) * 32768 + c7 * 4096, 4096);
            }
#pragma unroll 1
            for (int i = 0; i < 8; i++) { wait_until(tab[32 + i]); prefetch_l2((const char*)P.wo + c * 5120 + i * 655360, 5120); }
#pragma unroll 1
            for (int i = 0; i < 5; i++) { wait_until(tab[40 + i]); prefetch_l2((const char*)P.w1 + c * 3456 + i * 442368, 3456); }
#pragma unroll 1
            for (int i = 0; i < (c < 96 ? 7 : 6); i++) { wait_until(tab[45 + i]); prefetch_l2((const char*)P.w2 + c * 2560 + i * 327680, 2560); }
        }
        return;
    }
    if (w == 16) {
        const uint32_t t0 = gtime();
        if (lane == 0) {
            asm volatile("prefetch.tensormap [%0];" :: "l"(&map_v) : "memory");
            asm volatile("prefetch.tensormap [%0];" :: "l"(is_f2 ? &map_w2 : &map_wo) : "memory");
            asm volatile("prefetch.tensormap [%0];" :: "l"(&map_w1) : "memory");
#pragma unroll
            for (int i = 0; i < NBAR; i++) mbar_init(bars + 8 * i, 1);
            asm volatile("fence.mbarrier_init.release.cluster;" ::: "memory");
        }
        volatile uint32_t* tab = (volatile uint32_t*)(sm + SM_TAB + 256);
        tab[lane] = t0 + P.ld[lane]; if (lane < NSTEP - 32) tab[32 + lane] = t0 + P.ld[32 + lane];
        __syncwarp();
        bar_arrive(1, 544);
        if (lane == 0) {
            const int s0 = (h & 2) * 4, rot = (h >> 2) * 2 + (h & 1);
#pragma unroll 1
            for (int i = 0; i < 8; i++) {
                wait_until(tab[s0 + i]);
                const int e = (i + rot) & 7;
                uint32_t b = bars + 8 * (B_K + e);
                mbar_expect_tx(b, 8192);
                bulk_g2s(sb + SM_K + e * 8192, (const char*)P.kc + kv_off + e * 32768 + r * 8192, 8192, b);
            }
#pragma unroll 1
            for (int i = 0; i < 8; i++) {
                wait_until(tab[16 + s0 + i]);
                const int e = (i + rot) & 7;
                uint32_t b = bars + 8 * (B_V + e);
                mbar_expect_tx(b, 8192);
                tma2d(sb + SM_V + e * 8192, &map_v, r * 32, h * SK + (SK - WIN) + e * 128, b);
            }
            if (is_wo) {
#pragma unroll 1
                for (int i = 0; i < 8; i++) {
                    wait_until(tab[32 + i]);
                    uint32_t b = bars + 8 * (B_WO + i);
                    mbar_expect_tx(b, 8192);
                    tma2d(sb + SM_WO + i * 8192, &map_wo, ng * 32, i * 512 + kg * 128, b);
                }
            }
            if (is_f1) {
                mbar_wait(bars + 8 * B_KFREE);
#pragma unroll 1
                for (int i = 0; i < 5; i++) {
                    wait_until(tab[40 + i]);
                    uint32_t b = bars + 8 * (B_W1 + i);
                    mbar_expect_tx(b, 8192);
                    tma2d(sb + SM_K + i * 8192, &map_w1, fi * 32, i * 128, b);
                }
            } else if (is_f2) {
#pragma unroll 1
                for (int i = 0; i < 7; i++) {
                    wait_until(tab[45 + i]);
                    uint32_t b = bars + 8 * (B_WO + i);
                    mbar_expect_tx(b, 8192);
                    tma2d(sb + SM_WO + i * 8192, &map_w2, fi * 16, i * 256, b);
                }
            }
        }
        return;
    }

    float* red = (float*)(sm + SM_RED);
    float* mw = (float*)(sm + SM_MW);
    float* lw = (float*)(sm + SM_LW);
    const int g = lane >> 2, tq = lane & 3;
    const int selsh = (g & 1) << 4;

    {
        int o = -1;
        if (w < 4) o = A_QX + c * 128 + t;
        else if (w < 12) o = a_sx(h, (w - 4) * 128 + r * 32 + lane);
        else if (w < 14) { if (is_wo) o = a_hp(w - 12, kg, ng * 32 + lane); }
        else if (w == 14) { if (is_f1) o = a_h1(lane >> 4, fi >> 2, (fi & 3) * 16 + (lane & 15)); }
        if (o >= 0) st_rlx1(A + o, 0u);
    }
    uint32_t tag, tag2;
    {
        bar_sync(6, 544);
        uint32_t bs[5];
#pragma unroll
        for (int i = 0; i < 5; i++) bs[i] = (uint32_t)((const unsigned short*)(sm + SM_XN))[row0 + 4 * i] << selsh;
        float d1[4] = {0.f, 0.f, 0.f, 0.f}, d2[4] = {0.f, 0.f, 0.f, 0.f};
        mma(d1, wv[0].x, wv[0].y, wv[1].x, wv[1].y, bs[0], bs[1]); mma(d2, wv[0].z, wv[0].w, wv[1].z, wv[1].w, bs[0], bs[1]);
        mma(d1, wv[2].x, wv[2].y, wv[3].x, wv[3].y, bs[2], bs[3]); mma(d2, wv[2].z, wv[2].w, wv[3].z, wv[3].w, bs[2], bs[3]);
        mma(d1, wv[4].x, wv[4].y, 0u, 0u, bs[4], 0u);              mma(d2, wv[4].z, wv[4].w, 0u, 0u, bs[4], 0u);
        if (tq < 2) *(float4*)(red + (w >> 1) * 128 + (w & 1) * 64 + g * 8 + tq * 4) =
            tq ? make_float4(d2[0], d2[1], d2[2], d2[3]) : make_float4(d1[0], d1[1], d1[2], d1[3]);
        bar_sync(1, 544);
        tag = *(volatile uint32_t*)(sm + SM_EP) + 1u;
        tag2 = ((tag & 1u) << 15) | ((tag & 2u) << 30);
        if (w < 4) {
            float s2 = 0.f;
#pragma unroll
            for (int i = 0; i < 8; i++) s2 += red[i * 128 + t];
            st_rlx1(A + A_QX + c * 128 + t, tagw(s2, tag));
            const uint32_t* p = A + A_QX + h * 512 + t;
            uint4 v; int it = 0;
            do { v.x = ld_rlx1(p); v.y = ld_rlx1(p + 128); v.z = ld_rlx1(p + 256); v.w = ld_rlx1(p + 384); } while (__any_sync(FULL, bad4(v, tag)) && ++it < SPIN_MAX);
            ((unsigned short*)(sm + SM_QS))[t] = (unsigned short)pack2((untag(v.x) + untag(v.y)) + (untag(v.z) + untag(v.w)), 0.f);
        }
        bar_sync(1, 512);
    }

    int side;
    const bool tb0 = tq & 1, tb1 = tq & 2;
    uint32_t po = sb + SM_RED + (((tq >> 1) * 16 + g) * 36 + w * 2 + (tq & 1)) * 4;
    {
        const int ch0 = ((g & 1) * 4 + tq) * 16, ch1 = ch0 ^ 64;
        const uint4 q00 = *(const uint4*)(sm + SM_QS + ch0), q01 = *(const uint4*)(sm + SM_QS + ch1);
        const uint4 q10 = *(const uint4*)(sm + SM_QS + 128 + ch0), q11 = *(const uint4*)(sm + SM_QS + 128 + ch1);
        mbar_wait(bars + 8 * (B_K + (w >> 1)));
        const unsigned char* kp = sm + SM_K + (w * 16 + g) * 256;
        float sa[4] = {0.f, 0.f, 0.f, 0.f}, sb2[4] = {0.f, 0.f, 0.f, 0.f};
#define SCORE_STEP(off, Q) { const uint4 X = *(const uint4*)(kp + (off)), Y = *(const uint4*)(kp + 2048 + (off)); \
        mma(sa, X.x, Y.x, X.y, Y.y, Q.x, Q.y); mma(sb2, X.z, Y.z, X.w, Y.w, Q.z, Q.w); }
        SCORE_STEP(ch0, q00) SCORE_STEP(ch1, q01) SCORE_STEP(128 + ch0, q10) SCORE_STEP(128 + ch1, q11)
        float s0 = (g & 1) ? sa[1] + sb2[1] : sa[0] + sb2[0];
        float s1 = (g & 1) ? sa[3] + sb2[3] : sa[2] + sb2[2];
        s0 = bfr(bfr(s0) * 0.08838834764831845f);
        s1 = bfr(bfr(s1) * 0.08838834764831845f);
        {
            uint32_t old = 0;
            uint32_t* p = A + a_sx(h, (w >> 1) * 128 + r * 32 + (w & 1) * 16 + perm16(g + 8 * tq));
            const uint32_t val = __float_as_uint(tq ? s1 : s0) | tag, c0 = clk32();
            if (tq < 2) asm volatile("atom.relaxed.gpu.global.exch.b32 %0, [%1], %2;" : "=r"(old) : "l"(p), "r"(val) : "memory");
            const uint32_t c1 = __any_sync(FULL, old == 4u) ? c0 : clk32();
            if (lane == 0) ((uint32_t*)(sm + SM_RT))[w] = c1 - c0;
        }
        uint4 v;
        { const uint32_t* p = A + a_sx(h, w * 64 + (lane & 15) * 4); int it = 0;
          while (v = ld_rlx4(p), __any_sync(FULL, bad4(v, tag)) && ++it < SPIN_MAX) delay(SC_BACKOFF); }
        float e0 = bf_hi(v.x), e1 = bf_hi(v.y), e2 = bf_hi(v.z), e3 = bf_hi(v.w);
        float m = fmaxf(fmaxf(e0, e1), fmaxf(e2, e3));
        m = fmaxf(m, shx(m, 1)); m = fmaxf(m, shx(m, 2)); m = fmaxf(m, shx(m, 4)); m = fmaxf(m, shx(m, 8));
        if (lane == 0) mw[w] = m;
        bar_sync(1, 512);
        if (t == 0) mbar_arrive(bars + 8 * B_KFREE);
        side = near_copy(sm, h, lane);
        float M = mw[lane & 15];
        M = fmaxf(M, shx(M, 1)); M = fmaxf(M, shx(M, 2)); M = fmaxf(M, shx(M, 4)); M = fmaxf(M, shx(M, 8));
        e0 = ex2((e0 - M) * LOG2E); e1 = ex2((e1 - M) * LOG2E); e2 = ex2((e2 - M) * LOG2E); e3 = ex2((e3 - M) * LOG2E);
        float l = (e0 + e1) + (e2 + e3);
        l += shx(l, 1); l += shx(l, 2); l += shx(l, 4); l += shx(l, 8);
        if (lane == 0) lw[w] = l;
        bar_sync(1, 512);
        float L = lw[lane & 15];
        L += shx(L, 1); L += shx(L, 2); L += shx(L, 4); L += shx(L, 8);
        L = rcp_apx(L);
        const uint32_t b0 = pack2(e0 * L, e1 * L), b1 = pack2(e2 * L, e3 * L);
        mbar_wait(bars + 8 * (B_V + (w >> 1)));
        uint32_t af[8][4]; float e[8][4];
        frags<true>(af, sb + SM_V + w * 4096, lane); zero8(e); mma8(e, af, b0, b1); store_part(e, po, tb0, tb1);
        bar_arrive(2, 544);
    }
    po += SM_PART2 - SM_RED; PIN(po);

    if (is_wo) {
        const uint32_t* p = A + a_o(side, kg, w * 64 + (lane & 15) * 4);
        uint4 va; uint32_t b0, b1;
        uint32_t af[8][4]; float e[8][4];
        mbar_wait(bars + 8 * (B_WO + (w >> 2)));
        uint32_t stale = 1;
        poll1<true>(va, [&](uint4& v) { if (stale) v = ld_rlx4(p); },
              [&](const uint4& v) { b0 = __byte_perm(v.x, v.y, 0x7632); b1 = __byte_perm(v.z, v.w, 0x7632); return stale = bad4(v, tag); },
              af, sb + SM_WO + w * 4096, bars + 8 * (B_WO + (w >> 1)), lane);
        zero8(e); mma8(e, af, b0, b1); store_part(e, po, tb0, tb1);
        bar_arrive(3, 544);
    }

    if (is_f1) {
        if (w < 10) {
            const uint32_t* xp = (const uint32_t*)(sm + SM_X) + w * 32 + (g & 3) * 8 + tq;
            const float x0 = bf_lo(xp[0]), x1 = bf_hi(xp[0]), x2 = bf_lo(xp[4]), x3 = bf_hi(xp[4]);
            uint32_t fo = sb + SM_FIN + ((16 * (tq & 1) + g) * FIN_PITCH + (tq >> 1) * 12 + w) * 4; PIN(fo);
            uint32_t so = sb + SM_ST + ((lane >> 1) * 12 + w) * 4; PIN(so);
            const bool stv = g < 4 && (tq & 1) == (g >> 1);
            const uint32_t* p = A + a_hp(side, (lane >> 4) * 2, w * 64 + (lane & 15) * 4);
            mbar_wait(bars + 8 * B_W1);
            uint32_t af[8][4], b0, b1;
            Set2 va;
            uint32_t sta = 1, stb = 1;
            poll1<true>(va, [&](Set2& v) { if (sta) v.a = ld_rlx4(p); if (stb) v.b = ld_rlx4(p + 4096); },
                  [&](const Set2& v) {
                      const uint32_t y0 = v.a.x ^ tag, y1 = v.a.y ^ tag, y2 = v.a.z ^ tag, y3 = v.a.w ^ tag, z0 = v.b.x ^ tag, z1 = v.b.y ^ tag, z2 = v.b.z ^ tag, z3 = v.b.w ^ tag;
                      float s0 = __uint_as_float(y0) + __uint_as_float(z0), s1 = __uint_as_float(y1) + __uint_as_float(z1);
                      float s2 = __uint_as_float(y2) + __uint_as_float(z2), s3 = __uint_as_float(y3) + __uint_as_float(z3);
                      s0 += shx(s0, 16); s1 += shx(s1, 16); s2 += shx(s2, 16); s3 += shx(s3, 16);
                      b0 = pack2(x0 + bfr(s0), x1 + bfr(s1)); b1 = pack2(x2 + bfr(s2), x3 + bfr(s3));
                      if (g >= 4) { b0 = 0x3f803f80u; b1 = 0x3f803f80u; }
                      sta = (y0 | y1 | y2 | y3) & 3u; stb = (z0 | z1 | z2 | z3) & 3u;
                      return sta | stb;
                  },
                  af, sb + SM_K + w * 4096, bars + 8 * (B_W1 + (w >> 1)), lane);
            float e[8][4], gm[4] = {0.f, 0.f, 0.f, 0.f};
            mma(gm, b0, 0u, b1, 0u, b0, b1);
            zero8(e); mma8(e, af, b0, b1);
            float st = stv ? ((g & 1) ? gm[1] : gm[0]) : 0.f;
            st += shx(st, 4);
            const float l0 = tb0 ? e[2][0] + e[3][1] : e[0][0] + e[1][1], h0 = tb0 ? e[2][2] + e[3][3] : e[0][2] + e[1][3];
            const float l1 = tb0 ? e[6][0] + e[7][1] : e[4][0] + e[5][1], h1 = tb0 ? e[6][2] + e[7][3] : e[4][2] + e[5][3];
            st += shx(st, 9);
            sts(fo, (tb0 ? l1 : l0) + shx(tb0 ? l0 : l1, 1));
            sts(fo + 8 * FIN_PITCH * 4, (tb0 ? h1 : h0) + shx(tb0 ? h0 : h1, 1));
            if (!(lane & 29)) sts(so, st);
            bar_arrive(4, 352);
        }
    } else if (is_f2) {
        if (w < 14) {
            const bool live = w < 13 || lane < 16;
            const uint32_t* p = A + a_h1(side, w, (live ? lane : lane - 16) * 2);
            const uint32_t msk = live ? 0x7fff7fffu : 0u;
            uint32_t qo = sb + SM_PART2 + (g * 60 + w * 4 + tq) * 4; PIN(qo);
            mbar_wait(bars + 8 * (B_WO + 3));
            uint32_t af[8][4]; uint2 v;
            uint32_t stale = 1;
            poll1<false>(v, [&](uint2& u) { if (stale) u = ld_rlx2(p); }, [&](const uint2& u) { return stale = ((u.x ^ tag2) | (u.y ^ tag2)) & 0x80008000u; },
                         af, sb + SM_WO + w * 4096, bars + 8 * (B_WO + (w >> 1)), lane);
            float e[8][4];
            zero8(e);
            mma8(e, af, v.x & msk, v.y & msk);
            const float l0 = tb0 ? e[2][0] + e[3][1] : e[0][0] + e[1][1], h0 = tb0 ? e[2][2] + e[3][3] : e[0][2] + e[1][3];
            const float l1 = tb0 ? e[6][0] + e[7][1] : e[4][0] + e[5][1], h1 = tb0 ? e[6][2] + e[7][3] : e[4][2] + e[5][3];
            sts(qo, tb1 ? l1 : l0); sts(qo + 8 * 240, tb1 ? h1 : h0);
            bar_arrive(5, 480);
        }
    }
}

typedef CUresult (*EncodeFn)(CUtensorMap*, CUtensorMapDataType, cuuint32_t, void*, const cuuint64_t*, const cuuint64_t*,
                             const cuuint32_t*, const cuuint32_t*, CUtensorMapInterleave, CUtensorMapSwizzle,
                             CUtensorMapL2promotion, CUtensorMapFloatOOBfill);
float g_par[13] = {1200.f, 164.f, 164.f, 400.f, 164.f, 0.f, 250.f, 500.f, 500.f, 200.f, 100.f, 0.f, 0.f};

void make_map(EncodeFn enc, CUtensorMap* m, void* base, int cols, int rows, int bc, int br, CUtensorMapSwizzle sw = CU_TENSOR_MAP_SWIZZLE_64B) {
    cuuint64_t gd[2] = {(cuuint64_t)cols, (cuuint64_t)rows}; cuuint64_t gs[1] = {(cuuint64_t)cols * 2};
    cuuint32_t bd[2] = {(cuuint32_t)bc, (cuuint32_t)br}; cuuint32_t es[2] = {1, 1};
    enc(m, CU_TENSOR_MAP_DATA_TYPE_BFLOAT16, 2, base, gd, gs, bd, es, CU_TENSOR_MAP_INTERLEAVE_NONE, sw,
        CU_TENSOR_MAP_L2_PROMOTION_L2_128B, CU_TENSOR_MAP_FLOAT_OOB_FILL_NONE);
}

}

extern "C" void kernel_launch(void* const* d_in, const int* in_sizes, int n_in, void* d_out, int out_size) {
    (void)in_sizes; (void)n_in; (void)out_size;
    static EncodeFn enc = nullptr;
    static uint32_t* arena = nullptr;
    if (!enc) {
        void* sym = nullptr;
        cudaGetSymbolAddress(&sym, g_arena);
        arena = (uint32_t*)(((uintptr_t)sym + 524287) & ~(uintptr_t)524287);
        cudaDriverEntryPointQueryResult qr;
        cudaGetDriverEntryPoint("cuTensorMapEncodeTiled", (void**)&enc, cudaEnableDefault, &qr);
        cudaFuncSetAttribute(fused_decode_kernel, cudaFuncAttributeMaxDynamicSharedMemorySize, SM_TOTAL);
    }
    CUtensorMap mv, mwo, mw1, mw2;
    make_map(enc, &mv, d_in[2], DH, NH * SK, 32, 128);
    make_map(enc, &mwo, d_in[4], D, NH * DH, 32, 128);
    make_map(enc, &mw1, d_in[6], DFF, D, 32, 128);
    make_map(enc, &mw2, d_in[7], D, DFF, 16, 256, CU_TENSOR_MAP_SWIZZLE_32B);
    Params P = {(const __nv_bfloat16*)d_in[0], (const __nv_bfloat16*)d_in[1], (const __nv_bfloat16*)d_in[2], (const __nv_bfloat16*)d_in[3],
                (const __nv_bfloat16*)d_in[4], (const __nv_bfloat16*)d_in[6], (const __nv_bfloat16*)d_in[7], (__nv_bfloat16*)d_out, arena};
    float t = g_par[0];
    for (int i = 0; i < NSTEP; i++) {
        if (i == 16) t += g_par[12];
        if (i == 32) t += g_par[11];
        if (i == 40) t += g_par[3];
        if (i == 45) t += g_par[5];
        P.pf[i] = (uint32_t)t;
        P.ld[i] = (uint32_t)(t + g_par[i < 32 ? 7 : i < 40 ? 8 : i < 45 ? 9 : 10]);
        t += i < 32 ? g_par[1] : i < 40 ? 1.25f * g_par[2] : i < 45 ? 0.84375f * g_par[4] : 0.625f * g_par[6];
    }
    fused_decode_kernel<<<NCTA, NTHREADS, SM_TOTAL, cudaStreamPerThread>>>(P, mv, mwo, mw1, mw2);
}
```

```cpp
#include <cuda_runtime.h>
#include <cuda_bf16.h>
#include <cuda.h>
#include <stdint.h>

namespace {

constexpr int D = 640, DH = 128, NH = 32, SK = 4096, WIN = 1024, DFF = 1728;
constexpr int NCTA = 128;
constexpr int NTHREADS = 608;

constexpr int SC_BACKOFF = 300;

constexpr int FIN_PITCH = 28;
constexpr int SM_K = 0;
constexpr int SM_V = 65536;
constexpr int SM_WO = 131072;
constexpr int SM_RED = SM_WO + 65536;
constexpr int SM_PART2 = SM_RED + 32 * 36 * 4;
constexpr int SM_FIN = SM_PART2 + 32 * 36 * 4;
constexpr int SM_ST = SM_FIN + 32 * FIN_PITCH * 4;
constexpr int SM_QS = SM_ST + 96;
constexpr int SM_X = SM_QS + 256;
constexpr int SM_XN = SM_X + 1280;
constexpr int SM_MW = SM_XN + 1280;
constexpr int SM_LW = SM_MW + 64;
constexpr int SM_RT = SM_LW + 64;
constexpr int SM_BAR = SM_RT + 64;
constexpr int SM_EP = SM_BAR + 256;
constexpr int SM_TAB = SM_EP + 32;
constexpr int SM_TOTAL = SM_TAB + 512;

constexpr int B_K = 0, B_V = 8, B_WO = 16, B_W1 = 24, B_KFREE = 29, NBAR = 30;
constexpr int NSTEP = 52;
constexpr int SPIN_MAX = 1 << 18;
constexpr unsigned FULL = 0xffffffffu;
constexpr float LOG2E = 1.4426950408889634f;

constexpr int A_QX = 16384;
constexpr int A_SX = A_QX + NCTA * 128;
constexpr int A_EP = A_SX + NH * WIN;
constexpr int A_WORDS = A_EP + 32;
__device__ uint32_t g_arena[A_WORDS + 131072];
__device__ __forceinline__ int a_sx(int head, int key) { return A_SX + (head >> 1) * 2048 + (key >> 9) * 1024 + (head & 1) * 512 + (key & 511); }
__device__ __forceinline__ int a_o(int s, int head, int i) { return (head & 3) * 4096 + s * 1024 + (head >> 2) * 128 + i; }
__device__ __forceinline__ int a_hp(int s, int k, int i) { return k * 4096 + (3 - s) * 1024 + i; }
__device__ __forceinline__ int a_h1(int s, int tile, int i) { return (tile >> 2) * 4096 + (3 - s) * 1024 + D + (tile & 3) * 64 + i; }

__device__ __forceinline__ uint32_t gtime() { uint32_t t; asm volatile("mov.u32 %0, %%globaltimer_lo;" : "=r"(t) :: "memory"); return t; }
__device__ __forceinline__ uint32_t clk32() { uint32_t t; asm volatile("mov.u32 %0, %%clock;" : "=r"(t) :: "memory"); return t; }
__device__ __forceinline__ uint32_t pack2(float lo, float hi) { uint32_t d; asm("cvt.rn.bf16x2.f32 %0, %1, %2;" : "=r"(d) : "f"(hi), "f"(lo)); return d; }
__device__ __forceinline__ float bfr(float x) { return __uint_as_float(pack2(0.f, x)); }
__device__ __forceinline__ float bf_lo(uint32_t w) { return __uint_as_float(w << 16); }
__device__ __forceinline__ float bf_hi(uint32_t w) { return __uint_as_float(w & 0xffff0000u); }
__device__ __forceinline__ uint32_t tagw(float v, uint32_t tag) { return (__float_as_uint(v) & 0xfffffffcu) | tag; }
__device__ __forceinline__ float untag(uint32_t w) { return __uint_as_float(w & 0xfffffffcu); }
__device__ __forceinline__ uint32_t bad4(const uint4& v, uint32_t tag) { return ((v.x ^ tag) | (v.y ^ tag) | (v.z ^ tag) | (v.w ^ tag)) & 3u; }
__device__ __forceinline__ int perm16(int i) { return (i & ~15) | ((i & 6) << 1) | ((i & 8) >> 2) | (i & 1); }

__device__ __forceinline__ void mbar_init(uint32_t bar, uint32_t cnt) { asm volatile("mbarrier.init.shared::cta.b64 [%0], %1;" :: "r"(bar), "r"(cnt) : "memory"); }
__device__ __forceinline__ void mbar_expect_tx(uint32_t bar, uint32_t bytes) { asm volatile("mbarrier.arrive.expect_tx.shared::cta.b64 _, [%0], %1;" :: "r"(bar), "r"(bytes) : "memory"); }
__device__ __forceinline__ void mbar_arrive(uint32_t bar) { asm volatile("mbarrier.arrive.shared::cta.b64 _, [%0];" :: "r"(bar) : "memory"); }
__device__ __forceinline__ void mbar_wait(uint32_t bar) {
    uint32_t done; int it = 0;
    do {
        asm volatile("{\n.reg .pred p;\nmbarrier.try_wait.parity.shared::cta.b64 p, [%1], 0, 20000;\nselp.u32 %0, 1, 0, p;\n}" : "=r"(done) : "r"(bar) : "memory");
    } while (!done && ++it < SPIN_MAX);
}
__device__ __forceinline__ bool mbar_test(uint32_t bar) {
    uint32_t done;
    asm volatile("{\n.reg .pred p;\nmbarrier.test_wait.parity.shared::cta.b64 p, [%1], 0;\nselp.u32 %0, 1, 0, p;\n}" : "=r"(done) : "r"(bar) : "memory");
    return __all_sync(0xffffffffu, done);
}
__device__ __forceinline__ uint64_t policy_evict_first() { uint64_t p; asm("createpolicy.fractional.L2::evict_first.b64 %0, 1.0;" : "=l"(p)); return p; }
__device__ __forceinline__ void bulk_g2s(uint32_t dst, const void* src, uint32_t bytes, uint32_t bar) {
    asm volatile("cp.async.bulk.shared::cluster.global.mbarrier::complete_tx::bytes [%0], [%1], %2, [%3];" :: "r"(dst), "l"(src), "r"(bytes), "r"(bar) : "memory");
}
__device__ __forceinline__ void tma2d(uint32_t dst, const CUtensorMap* m, int c0, int c1, uint32_t bar) {
    asm volatile("cp.async.bulk.tensor.2d.shared::cluster.global.mbarrier::complete_tx::bytes [%0], [%1, {%3, %4}], [%2];" :: "r"(dst), "l"(m), "r"(bar), "r"(c0), "r"(c1) : "memory");
}
__device__ __forceinline__ void prefetch_l2(const void* src, uint32_t bytes) {
    asm volatile("cp.async.bulk.prefetch.L2.global.L2::cache_hint [%0], %1, %2;" :: "l"(src), "r"(bytes), "l"(policy_evict_first()) : "memory");
}
__device__ __forceinline__ void wait_until(uint32_t tgt) {
    int it = 0;
    while ((int)(gtime() - tgt) < 0 && ++it < SPIN_MAX) {}
}
__device__ __forceinline__ void bar_sync(int id, int n) { asm volatile("bar.sync %0, %1;" :: "r"(id), "r"(n) : "memory"); }
__device__ __forceinline__ void bar_arrive(int id, int n) { asm volatile("bar.arrive %0, %1;" :: "r"(id), "r"(n) : "memory"); }
__device__ __forceinline__ uint4 ld_rlx4(const void* p) {
    uint4 v; asm volatile("ld.relaxed.gpu.global.v4.u32 {%0,%1,%2,%3}, [%4];" : "=r"(v.x), "=r"(v.y), "=r"(v.z), "=r"(v.w) : "l"(p) : "memory"); return v;
}
__device__ __forceinline__ uint2 ld_rlx2(const void* p) {
    uint2 v; asm volatile("ld.relaxed.gpu.global.v2.u32 {%0,%1}, [%2];" : "=r"(v.x), "=r"(v.y) : "l"(p) : "memory"); return v;
}
__device__ __forceinline__ uint32_t ld_rlx1(const void* p) {
    uint32_t v; asm volatile("ld.relaxed.gpu.global.u32 %0, [%1];" : "=r"(v) : "l"(p) : "memory"); return v;
}
__device__ __forceinline__ void st_rlx1(void* p, uint32_t v) { asm volatile("st.relaxed.gpu.global.u32 [%0], %1;" :: "l"(p), "r"(v) : "memory"); }
__device__ __forceinline__ float sqrt_apx(float x) { float y; asm("sqrt.approx.f32 %0, %1;" : "=f"(y) : "f"(x)); return y; }
__device__ __forceinline__ float ex2(float x) { float y; asm("ex2.approx.ftz.f32 %0, %1;" : "=f"(y) : "f"(x)); return y; }
__device__ __forceinline__ float rcp_apx(float x) { float y; asm("rcp.approx.ftz.f32 %0, %1;" : "=f"(y) : "f"(x)); return y; }
__device__ __forceinline__ float shx(float v, int m) { return __shfl_xor_sync(FULL, v, m); }
__device__ __forceinline__ void delay(uint32_t n) { uint32_t t0 = clk32(); while (clk32() - t0 < n) {} }
__device__ __forceinline__ float sum4(const float4& a) { return (a.x + a.y) + (a.z + a.w); }

__device__ __forceinline__ void mma(float* d, uint32_t a0, uint32_t a1, uint32_t a2, uint32_t a3, uint32_t b0, uint32_t b1) {
    asm("mma.sync.aligned.m16n8k16.row.col.f32.bf16.bf16.f32 {%0,%1,%2,%3}, {%4,%5,%6,%7}, {%8,%9}, {%0,%1,%2,%3};"
        : "+f"(d[0]), "+f"(d[1]), "+f"(d[2]), "+f"(d[3]) : "r"(a0), "r"(a1), "r"(a2), "r"(a3), "r"(b0), "r"(b1));
}
__device__ __forceinline__ void ldsm4t(uint32_t* r, uint32_t addr) {
    asm volatile("ldmatrix.sync.aligned.m8n8.x4.trans.shared.b16 {%0,%1,%2,%3}, [%4];" : "=r"(r[0]), "=r"(r[1]), "=r"(r[2]), "=r"(r[3]) : "r"(addr) : "memory");
}
template <bool W64>
__device__ __forceinline__ void frags(uint32_t (*af)[4], uint32_t tile, int lane) {
    const int row = (lane & 7) + 8 * (lane >> 4);
    if (W64) {
        const uint32_t ad = tile + row * 64 + ((((lane >> 3) & 1) ^ ((lane >> 1) & 3)) << 4);
#pragma unroll
        for (int j = 0; j < 8; j++) ldsm4t(af[j], (ad ^ ((j >> 2) << 5)) + (j & 3) * 1024);
    } else {
        const uint32_t ad = tile + row * 32 + ((((lane >> 3) ^ (lane >> 2)) & 1) << 4);
#pragma unroll
        for (int j = 0; j < 8; j++) ldsm4t(af[j], ad + j * 512);
    }
}
__device__ __forceinline__ void mma8(float (*e)[4], const uint32_t (*af)[4], uint32_t b0, uint32_t b1) {
#pragma unroll
    for (int j = 0; j < 8; j++) mma(e[j], af[j][0], af[j][1], af[j][2], af[j][3], b0, b1);
}
__device__ __forceinline__ void zero8(float (*e)[4]) {
#pragma unroll
    for (int j = 0; j < 8; j++) { e[j][0] = 0.f; e[j][1] = 0.f; e[j][2] = 0.f; e[j][3] = 0.f; }
}
#define PIN(x) asm volatile("" : "+r"(x))
#define PINL(x) asm volatile("" : "+l"(x))
__device__ __forceinline__ void sts(uint32_t addr, float v) { asm volatile("st.shared.f32 [%0], %1;" :: "r"(addr), "f"(v) : "memory"); }
__device__ __forceinline__ float4 lds4(uint32_t addr) {
    float4 v; asm volatile("ld.shared.v4.f32 {%0,%1,%2,%3}, [%4];" : "=f"(v.x), "=f"(v.y), "=f"(v.z), "=f"(v.w) : "r"(addr) : "memory"); return v;
}
__device__ __forceinline__ void store_part(float (*e)[4], uint32_t po, bool t0, bool t1) {
    const float l0 = t0 ? e[2][0] + e[3][1] : e[0][0] + e[1][1], h0 = t0 ? e[2][2] + e[3][3] : e[0][2] + e[1][3];
    const float l1 = t0 ? e[6][0] + e[7][1] : e[4][0] + e[5][1], h1 = t0 ? e[6][2] + e[7][3] : e[4][2] + e[5][3];
    sts(po, t1 ? l1 : l0); sts(po + 8 * 36 * 4, t1 ? h1 : h0);
}
__device__ __forceinline__ float rowsum32(uint32_t row) {
    const float4 a = lds4(row), b = lds4(row + 16), c = lds4(row + 32), d = lds4(row + 48), e = lds4(row + 64), f = lds4(row + 80), g = lds4(row + 96), h = lds4(row + 112);
    return ((sum4(a) + sum4(b)) + (sum4(c) + sum4(d))) + ((sum4(e) + sum4(f)) + (sum4(g) + sum4(h)));
}
template <bool W64, class Set, class Issue, class Proc>
__device__ __forceinline__ void poll1(Set& sa, Issue issue, Proc proc, uint32_t (*af)[4], uint32_t tile, uint32_t bar, int lane) {
    bool have = false, bad = true;
#pragma unroll 1
    for (int it = 0; it < SPIN_MAX; it++) {
        if (bad) issue(sa);
        if (!have) { have = mbar_test(bar); if (have) frags<W64>(af, tile, lane); }
        if (bad) bad = __any_sync(FULL, proc(sa));
        if (have && !bad) break;
    }
}
__device__ __forceinline__ int near_copy(const unsigned char* sm, int h, int lane) {
    uint32_t v = ((const uint32_t*)(sm + SM_RT))[lane & 15];
    v = min(v, __shfl_xor_sync(FULL, v, 1)); v = min(v, __shfl_xor_sync(FULL, v, 2)); v = min(v, __shfl_xor_sync(FULL, v, 4));
    const int second = __shfl_sync(FULL, v, 8) < __shfl_sync(FULL, v, 0);
    return (__popc((uint32_t)a_sx(h, 0) * 4u & 0xb3000u) & 1) ^ second;
}
struct Set2 { uint4 a, b; };

struct Params {
    const __nv_bfloat16 *x, *kc, *vc, *wq, *wo, *w1, *w2;
    __nv_bfloat16* out;
    uint32_t* arena;
    uint32_t pf[NSTEP], ld[NSTEP];
};

__global__ void __launch_bounds__(NTHREADS, 1)
fused_decode_kernel(const __grid_constant__ Params P, const __grid_constant__ CUtensorMap map_v, const __grid_constant__ CUtensorMap map_wo,
                    const __grid_constant__ CUtensorMap map_w1, const __grid_constant__ CUtensorMap map_w2)
{
    extern __shared__ __align__(1024) unsigned char sm[];
    const int t = threadIdx.x, lane = t & 31;
    const int c = blockIdx.x, h = c >> 2, r = c & 3;
    uint4 wv[5];
    const int row0 = r * 160 + (t >> 6) * 20 + (t & 3);
    if (t < 512) {
        const char* src = (const char*)P.wq + (size_t)row0 * (NH * DH * 2) + h * 256 + (t & 60) * 4;
#pragma unroll
        for (int i = 0; i < 5; i++)
            asm volatile("ld.global.nc.L1::no_allocate.L2::cache_hint.v4.u32 {%0,%1,%2,%3}, [%4], %5;" : "=r"(wv[i].x), "=r"(wv[i].y), "=r"(wv[i].z), "=r"(wv[i].w) : "l"(src + (size_t)i * 4 * (NH * DH * 2)), "l"(policy_evict_first()) : "memory");
    }
    const int w = __shfl_sync(FULL, t >> 5, 0);
    const uint32_t sb = (uint32_t)__cvta_generic_to_shared(sm);
    const uint32_t bars = sb + SM_BAR;
    const int cq = c >> 4, cj = c & 15, c7 = c & 7;
    const int kg = c >> 5, ng = ((c >> 3) & 3) * 5 + c7;
    const bool is_wo = c7 < 5, is_f2 = c7 > 5 || cj == 5, is_f1 = !is_f2 && c7 >= 2 && !(cj == 13 && (cq & 3) == 2);
    const int fi = is_f2 ? cq * 5 + (cj < 8 ? cj - 5 : cj - 11) : cq * 7 - (cq > 2) - (cq > 6) + (cj < 8 ? cj - 2 : cj - 7);
    uint32_t* const A = P.arena;
    const size_t kv_off = ((size_t)h * SK + (SK - WIN)) * 256;

    if (w == 18) {
        uint32_t ep;
        uint32_t* po = A + a_o(0, h, r * 32 + perm16(lane)); PINL(po);
        {
            uint2 xs[5];
#pragma unroll
            for (int i = 0; i < 5; i++) xs[i] = __ldg((const uint2*)(P.x + lane * 4 + 128 * i));
            ep = ld_rlx1(A + A_EP);
            st_rlx1(po, 0u); st_rlx1(po + 1024, 0u);
            float s = 0.f;
#pragma unroll
            for (int i = 0; i < 5; i++) s += (bf_lo(xs[i].x) + bf_hi(xs[i].x)) + (bf_lo(xs[i].y) + bf_hi(xs[i].y));
#pragma unroll
            for (int m = 16; m; m >>= 1) s += shx(s, m);
            const float mean = s * (1.0f / D);
            float ss = 0.f;
#pragma unroll
            for (int i = 0; i < 5; i++) {
                float a = bf_lo(xs[i].x) - mean, b = bf_hi(xs[i].x) - mean, e = bf_lo(xs[i].y) - mean, f = bf_hi(xs[i].y) - mean;
                ss += (a * a + b * b) + (e * e + f * f);
            }
#pragma unroll
            for (int m = 16; m; m >>= 1) ss += shx(ss, m);
            const float mb = bfr(mean), rs = rcp_apx(bfr(sqrt_apx(bfr(bfr(ss * (1.0f / D)) + 1e-5f))));
#pragma unroll
            for (int i = 0; i < 5; i++) {
                const uint32_t d0 = pack2(bf_lo(xs[i].x) - mb, bf_hi(xs[i].x) - mb), d1 = pack2(bf_lo(xs[i].y) - mb, bf_hi(xs[i].y) - mb);
                *(uint2*)(sm + SM_XN + lane * 8 + i * 256) = make_uint2(pack2(bf_lo(d0) * rs, bf_hi(d0) * rs), pack2(bf_lo(d1) * rs, bf_hi(d1) * rs));
                *(uint2*)(sm + SM_X + lane * 8 + i * 256) = xs[i];
            }
            *(uint32_t*)(sm + SM_EP) = ep;
            bar_arrive(6, 544);
        }
        const uint32_t tag = ep + 1u, tag2 = ((tag & 1u) << 15) | ((tag & 2u) << 30);
        uint32_t row = sb + SM_RED + lane * 144; PIN(row);
        bar_sync(2, 544);
        { const uint32_t tv = pack2(0.f, rowsum32(row)) | tag; st_rlx1(po, tv); st_rlx1(po + 1024, tv); }
        if (is_wo) {
            uint32_t* ph = A + a_hp(1, kg, ng * 32 + perm16(lane)); PINL(ph);
            bar_sync(3, 544);
            const uint32_t tv = tagw(rowsum32(row + (SM_PART2 - SM_RED)), tag);
            st_rlx1(ph, tv); st_rlx1(ph + 1024, tv);
        }
        if (is_f1) {
            uint32_t* mbox = A + a_h1(lane & 1, fi >> 2, (fi & 3) * 16 + (perm16(lane) >> 1)); PINL(mbox);
            uint32_t sp = sb + SM_ST + (lane & 1) * 48, fp = sb + SM_FIN + lane * (FIN_PITCH * 4); PIN(sp); PIN(fp);
            bar_sync(4, 352);
            const float4 s0 = lds4(sp), s1 = lds4(sp + 16), s2 = lds4(sp + 32);
            const float4 a0 = lds4(fp), a1 = lds4(fp + 16), a2 = lds4(fp + 32), a3 = lds4(fp + 48), a4 = lds4(fp + 64), a5 = lds4(fp + 80);
            const float sa = (sum4(s0) + sum4(s1)) + (s2.x + s2.y), sb2 = shx(sa, 1);
            const float acc = (sum4(a0) + sum4(a1)) + (a2.x + a2.y), cs = (sum4(a3) + sum4(a4)) + (a5.x + a5.y);
            const float mean = ((lane & 1) ? sa : sb2) * (1.0f / D);
            const float var = fmaxf(((lane & 1) ? sb2 : sa) * (1.0f / D) - mean * mean, 0.f);
            const float rs = rcp_apx(bfr(sqrt_apx(bfr(bfr(var) + 1e-5f))));
            const float hid = fmaxf((acc - bfr(mean) * cs) * rs, 0.f), oth = shx(hid, 1);
            st_rlx1(mbox, (((lane & 1) ? pack2(oth, hid) : pack2(hid, oth)) & 0x7fff7fffu) | tag2);
        } else if (is_f2) {
            const int col = fi * 16 + (lane & 15);
            unsigned short* op = (unsigned short*)P.out + col; PINL(op);
            uint32_t fp = sb + SM_PART2 + (lane & 15) * 240 + (lane >> 4) * 112; PIN(fp);
            const float xv = __uint_as_float((uint32_t)((const unsigned short*)(sm + SM_X))[col] << 16);
            const uint32_t* p = A + a_hp(near_copy(sm, h, lane), (lane >> 4) * 2, perm16(col));
            uint32_t u0, u1; int it = 0;
            mbar_wait(bars + 8 * (B_WO + 2));
            while (u0 = ld_rlx1(p), u1 = ld_rlx1(p + 4096), __any_sync(FULL, ((u0 ^ tag) | (u1 ^ tag)) & 3u) && ++it < SPIN_MAX) delay(200);
            float hs = untag(u0) + untag(u1);
            hs += shx(hs, 16);
            const float hval = bfr(xv + bfr(hs));
            bar_sync(5, 480);
            const float4 a0 = lds4(fp), a1 = lds4(fp + 16), a2 = lds4(fp + 32), a3 = lds4(fp + 48), a4 = lds4(fp + 64), a5 = lds4(fp + 80), a6 = lds4(fp + 96);
            float sum = ((sum4(a0) + sum4(a1)) + (sum4(a2) + sum4(a3))) + ((sum4(a4) + sum4(a5)) + sum4(a6));
            sum += shx(sum, 16);
            if (lane < 16) *op = (unsigned short)pack2(hval + bfr(sum), 0.f);
            if (fi == 0 && lane == 0) st_rlx1(A + A_EP, ep >= 2u ? 0u : ep + 1u);
        }
        return;
    }
    if (w == 17) {
        const uint32_t t0 = gtime();
        volatile uint32_t* tab = (volatile uint32_t*)(sm + SM_TAB);
        tab[lane] = t0 + P.pf[lane]; if (lane < NSTEP - 32) tab[32 + lane] = t0 + P.pf[32 + lane];
        __syncwarp();
        if (lane == 0) {
#pragma unroll 1
            for (int i = 0; i < 32; i++) {
                wait_until(tab[i]);
                prefetch_l2((const char*)(i < 16 ? P.kc : P.vc) + (size_t)((cq * 4 + ((i >> 3) & 1) * 2 + ((c >> 3) & 1)) * 32 + 24 + ((i + (c >> 3)) & 7)) * 32768 + c7 * 4096, 4096);
            }
#pragma unroll 1
            for (int i = 0; i < 8; i++) { wait_until(tab[32 + i]); prefetch_l2((const char*)P.wo + c * 5120 + i * 655360, 5120); }
#pragma unroll 1
            for (int i = 0; i < 5; i++) { wait_until(tab[40 + i]); prefetch_l2((const char*)P.w1 + c * 3456 + i * 442368, 3456); }
#pragma unroll 1
            for (int i = 0; i < (c < 96 ? 7 : 6); i++) { wait_until(tab[45 + i]); prefetch_l2((const char*)P.w2 + c * 2560 + i * 327680, 2560); }
        }
        return;
    }
    if (w == 16) {
        const uint32_t t0 = gtime();
        if (lane == 0) {
            asm volatile("prefetch.tensormap [%0];" :: "l"(&map_v) : "memory");
            asm volatile("prefetch.tensormap [%0];" :: "l"(is_f2 ? &map_w2 : &map_wo) : "memory");
            asm volatile("prefetch.tensormap [%0];" :: "l"(&map_w1) : "memory");
#pragma unroll
            for (int i = 0; i < NBAR; i++) mbar_init(bars + 8 * i, 1);
            asm volatile("fence.mbarrier_init.release.cluster;" ::: "memory");
        }
        volatile uint32_t* tab = (volatile uint32_t*)(sm + SM_TAB + 256);
        tab[lane] = t0 + P.ld[lane]; if (lane < NSTEP - 32) tab[32 + lane] = t0 + P.ld[32 + lane];
        __syncwarp();
        bar_arrive(1, 544);
        if (lane == 0) {
            const int s0 = (h & 2) * 4, rot = (h >> 2) * 2 + (h & 1);
#pragma unroll 1
            for (int i = 0; i < 8; i++) {
                wait_until(tab[s0 + i]);
                const int e = (i + rot) & 7;
                uint32_t b = bars + 8 * (B_K + e);
                mbar_expect_tx(b, 8192);
                bulk_g2s(sb + SM_K + e * 8192, (const char*)P.kc + kv_off + e * 32768 + r * 8192, 8192, b);
            }
#pragma unroll 1
            for (int i = 0; i < 8; i++) {
                wait_until(tab[16 + s0 + i]);
                const int e = (i + rot) & 7;
                uint32_t b = bars + 8 * (B_V + e);
                mbar_expect_tx(b, 8192);
                tma2d(sb + SM_V + e * 8192, &map_v, r * 32, h * SK + (SK - WIN) + e * 128, b);
            }
            if (is_wo) {
#pragma unroll 1
                for (int i = 0; i < 8; i++) {
                    wait_until(tab[32 + i]);
                    uint32_t b = bars + 8 * (B_WO + i);
                    mbar_expect_tx(b, 8192);
                    tma2d(sb + SM_WO + i * 8192, &map_wo, ng * 32, i * 512 + kg * 128, b);
                }
            }
            if (is_f1) {
                mbar_wait(bars + 8 * B_KFREE);
#pragma unroll 1
                for (int i = 0; i < 5; i++) {
                    wait_until(tab[40 + i]);
                    uint32_t b = bars + 8 * (B_W1 + i);
                    mbar_expect_tx(b, 8192);
                    tma2d(sb + SM_K + i * 8192, &map_w1, fi * 32, i * 128, b);
                }
            } else if (is_f2) {
#pragma unroll 1
                for (int i = 0; i < 7; i++) {
                    wait_until(tab[45 + i]);
                    uint32_t b = bars + 8 * (B_WO + i);
                    mbar_expect_tx(b, 8192);
                    tma2d(sb + SM_WO + i * 8192, &map_w2, fi * 16, i * 256, b);
                }
            }
        }
        return;
    }

    float* red = (float*)(sm + SM_RED);
    float* mw = (float*)(sm + SM_MW);
    float* lw = (float*)(sm + SM_LW);
    const int g = lane >> 2, tq = lane & 3;
    const int selsh = (g & 1) << 4;

    {
        int o = -1;
        if (w < 4) o = A_QX + c * 128 + t;
        else if (w < 12) o = a_sx(h, (w - 4) * 128 + r * 32 + lane);
        else if (w < 14) { if (is_wo) o = a_hp(w - 12, kg, ng * 32 + lane); }
        else if (w == 14) { if (is_f1) o = a_h1(lane >> 4, fi >> 2, (fi & 3) * 16 + (lane & 15)); }
        if (o >= 0) st_rlx1(A + o, 0u);
    }
    uint32_t tag, tag2;
    {
        bar_sync(6, 544);
        uint32_t bs[5];
#pragma unroll
        for (int i = 0; i < 5; i++) bs[i] = (uint32_t)((const unsigned short*)(sm + SM_XN))[row0 + 4 * i] << selsh;
        float d1[4] = {0.f, 0.f, 0.f, 0.f}, d2[4] = {0.f, 0.f, 0.f, 0.f};
        mma(d1, wv[0].x, wv[0].y, wv[1].x, wv[1].y, bs[0], bs[1]); mma(d2, wv[0].z, wv[0].w, wv[1].z, wv[1].w, bs[0], bs[1]);
        mma(d1, wv[2].x, wv[2].y, wv[3].x, wv[3].y, bs[2], bs[3]); mma(d2, wv[2].z, wv[2].w, wv[3].z, wv[3].w, bs[2], bs[3]);
        mma(d1, wv[4].x, wv[4].y, 0u, 0u, bs[4], 0u);              mma(d2, wv[4].z, wv[4].w, 0u, 0u, bs[4], 0u);
        if (tq < 2) *(float4*)(red + (w >> 1) * 128 + (w & 1) * 64 + g * 8 + tq * 4) =
            tq ? make_float4(d2[0], d2[1], d2[2], d2[3]) : make_float4(d1[0], d1[1], d1[2], d1[3]);
        bar_sync(1, 544);
        tag = *(volatile uint32_t*)(sm + SM_EP) + 1u;
        tag2 = ((tag & 1u) << 15) | ((tag & 2u) << 30);
        if (w < 4) {
            float s2 = 0.f;
#pragma unroll
            for (int i = 0; i < 8; i++) s2 += red[i * 128 + t];
            st_rlx1(A + A_QX + c * 128 + t, tagw(s2, tag));
            const uint32_t* p = A + A_QX + h * 512 + t;
            uint4 v; int it = 0;
            mbar_wait(bars + 8 * (B_K + (((h >> 2) * 2 + (h & 1) + 5) & 7)));
            do { v.x = ld_rlx1(p); v.y = ld_rlx1(p + 128); v.z = ld_rlx1(p + 256); v.w = ld_rlx1(p + 384); } while (__any_sync(FULL, bad4(v, tag)) && ++it < SPIN_MAX);
            ((unsigned short*)(sm + SM_QS))[t] = (unsigned short)pack2((untag(v.x) + untag(v.y)) + (untag(v.z) + untag(v.w)), 0.f);
        }
        bar_sync(1, 512);
    }

    int side;
    const bool tb0 = tq & 1, tb1 = tq & 2;
    uint32_t po = sb + SM_RED + (((tq >> 1) * 16 + g) * 36 + w * 2 + (tq & 1)) * 4;
    {
        const int ch0 = ((g & 1) * 4 + tq) * 16, ch1 = ch0 ^ 64;
        const uint4 q00 = *(const uint4*)(sm + SM_QS + ch0), q01 = *(const uint4*)(sm + SM_QS + ch1);
        const uint4 q10 = *(const uint4*)(sm + SM_QS + 128 + ch0), q11 = *(const uint4*)(sm + SM_QS + 128 + ch1);
        mbar_wait(bars + 8 * (B_K + (w >> 1)));
        const unsigned char* kp = sm + SM_K + (w * 16 + g) * 256;
        float sa[4] = {0.f, 0.f, 0.f, 0.f}, sb2[4] = {0.f, 0.f, 0.f, 0.f};
#define SCORE_STEP(off, Q) { const uint4 X = *(const uint4*)(kp + (off)), Y = *(const uint4*)(kp + 2048 + (off)); \
        mma(sa, X.x, Y.x, X.y, Y.y, Q.x, Q.y); mma(sb2, X.z, Y.z, X.w, Y.w, Q.z, Q.w); }
        SCORE_STEP(ch0, q00) SCORE_STEP(ch1, q01) SCORE_STEP(128 + ch0, q10) SCORE_STEP(128 + ch1, q11)
        float s0 = (g & 1) ? sa[1] + sb2[1] : sa[0] + sb2[0];
        float s1 = (g & 1) ? sa[3] + sb2[3] : sa[2] + sb2[2];
        s0 = bfr(bfr(s0) * 0.08838834764831845f);
        s1 = bfr(bfr(s1) * 0.08838834764831845f);
        {
            uint32_t old = 0;
            uint32_t* p = A + a_sx(h, (w >> 1) * 128 + r * 32 + (w & 1) * 16 + perm16(g + 8 * tq));
            const uint32_t val = __float_as_uint(tq ? s1 : s0) | tag, c0 = clk32();
            if (tq < 2) asm volatile("atom.relaxed.gpu.global.exch.b32 %0, [%1], %2;" : "=r"(old) : "l"(p), "r"(val) : "memory");
            const uint32_t c1 = __any_sync(FULL, old == 4u) ? c0 : clk32();
            if (lane == 0) ((uint32_t*)(sm + SM_RT))[w] = c1 - c0;
        }
        uint4 v;
        { const uint32_t* p = A + a_sx(h, w * 64 + (lane & 15) * 4); int it = 0;
          while (v = ld_rlx4(p), __any_sync(FULL, bad4(v, tag)) && ++it < SPIN_MAX) delay(SC_BACKOFF); }
        float e0 = bf_hi(v.x), e1 = bf_hi(v.y), e2 = bf_hi(v.z), e3 = bf_hi(v.w);
        float m = fmaxf(fmaxf(e0, e1), fmaxf(e2, e3));
        m = fmaxf(m, shx(m, 1)); m = fmaxf(m, shx(m, 2)); m = fmaxf(m, shx(m, 4)); m = fmaxf(m, shx(m, 8));
        if (lane == 0) mw[w] = m;
        bar_sync(1, 512);
        if (t == 0) mbar_arrive(bars + 8 * B_KFREE);
        side = near_copy(sm, h, lane);
        float M = mw[lane & 15];
        M = fmaxf(M, shx(M, 1)); M = fmaxf(M, shx(M, 2)); M = fmaxf(M, shx(M, 4)); M = fmaxf(M, shx(M, 8));
        e0 = ex2((e0 - M) * LOG2E); e1 = ex2((e1 - M) * LOG2E); e2 = ex2((e2 - M) * LOG2E); e3 = ex2((e3 - M) * LOG2E);
        float l = (e0 + e1) + (e2 + e3);
        l += shx(l, 1); l += shx(l, 2); l += shx(l, 4); l += shx(l, 8);
        if (lane == 0) lw[w] = l;
        bar_sync(1, 512);
        float L = lw[lane & 15];
        L += shx(L, 1); L += shx(L, 2); L += shx(L, 4); L += shx(L, 8);
        L = rcp_apx(L);
        const uint32_t b0 = pack2(e0 * L, e1 * L), b1 = pack2(e2 * L, e3 * L);
        mbar_wait(bars + 8 * (B_V + (w >> 1)));
        uint32_t af[8][4]; float e[8][4];
        frags<true>(af, sb + SM_V + w * 4096, lane); zero8(e); mma8(e, af, b0, b1); store_part(e, po, tb0, tb1);
        bar_arrive(2, 544);
    }
    po += SM_PART2 - SM_RED; PIN(po);

    if (is_wo) {
        const uint32_t* p = A + a_o(side, kg, w * 64 + (lane & 15) * 4);
        uint4 va; uint32_t b0, b1;
        uint32_t af[8][4]; float e[8][4];
        mbar_wait(bars + 8 * (B_WO + (w >> 2)));
        uint32_t stale = 1;
        poll1<true>(va, [&](uint4& v) { if (stale) v = ld_rlx4(p); },
              [&](const uint4& v) { b0 = __byte_perm(v.x, v.y, 0x7632); b1 = __byte_perm(v.z, v.w, 0x7632); return stale = bad4(v, tag); },
              af, sb + SM_WO + w * 4096, bars + 8 * (B_WO + (w >> 1)), lane);
        zero8(e); mma8(e, af, b0, b1); store_part(e, po, tb0, tb1);
        bar_arrive(3, 544);
    }

    if (is_f1) {
        if (w < 10) {
            const uint32_t* xp = (const uint32_t*)(sm + SM_X) + w * 32 + (g & 3) * 8 + tq;
            const float x0 = bf_lo(xp[0]), x1 = bf_hi(xp[0]), x2 = bf_lo(xp[4]), x3 = bf_hi(xp[4]);
            uint32_t fo = sb + SM_FIN + ((16 * (tq & 1) + g) * FIN_PITCH + (tq >> 1) * 12 + w) * 4; PIN(fo);
            uint32_t so = sb + SM_ST + ((lane >> 1) * 12 + w) * 4; PIN(so);
            const bool stv = g < 4 && (tq & 1) == (g >> 1);
            const uint32_t* p = A + a_hp(side, (lane >> 4) * 2, w * 64 + (lane & 15) * 4);
            mbar_wait(bars + 8 * B_W1);
            uint32_t af[8][4], b0, b1;
            Set2 va;
            uint32_t sta = 1, stb = 1;
            poll1<true>(va, [&](Set2& v) { if (sta) v.a = ld_rlx4(p); if (stb) v.b = ld_rlx4(p + 4096); },
                  [&](const Set2& v) {
                      const uint32_t y0 = v.a.x ^ tag, y1 = v.a.y ^ tag, y2 = v.a.z ^ tag, y3 = v.a.w ^ tag, z0 = v.b.x ^ tag, z1 = v.b.y ^ tag, z2 = v.b.z ^ tag, z3 = v.b.w ^ tag;
                      float s0 = __uint_as_float(y0) + __uint_as_float(z0), s1 = __uint_as_float(y1) + __uint_as_float(z1);
                      float s2 = __uint_as_float(y2) + __uint_as_float(z2), s3 = __uint_as_float(y3) + __uint_as_float(z3);
                      s0 += shx(s0, 16); s1 += shx(s1, 16); s2 += shx(s2, 16); s3 += shx(s3, 16);
                      b0 = pack2(x0 + bfr(s0), x1 + bfr(s1)); b1 = pack2(x2 + bfr(s2), x3 + bfr(s3));
                      if (g >= 4) { b0 = 0x3f803f80u; b1 = 0x3f803f80u; }
                      sta = (y0 | y1 | y2 | y3) & 3u; stb = (z0 | z1 | z2 | z3) & 3u;
                      return sta | stb;
                  },
                  af, sb + SM_K + w * 4096, bars + 8 * (B_W1 + (w >> 1)), lane);
            float e[8][4], gm[4] = {0.f, 0.f, 0.f, 0.f};
            mma(gm, b0, 0u, b1, 0u, b0, b1);
            zero8(e); mma8(e, af, b0, b1);
            float st = stv ? ((g & 1) ? gm[1] : gm[0]) : 0.f;
            st += shx(st, 4);
            const float l0 = tb0 ? e[2][0] + e[3][1] : e[0][0] + e[1][1], h0 = tb0 ? e[2][2] + e[3][3] : e[0][2] + e[1][3];
            const float l1 = tb0 ? e[6][0] + e[7][1] : e[4][0] + e[5][1], h1 = tb0 ? e[6][2] + e[7][3] : e[4][2] + e[5][3];
            st += shx(st, 9);
            sts(fo, (tb0 ? l1 : l0) + shx(tb0 ? l0 : l1, 1));
            sts(fo + 8 * FIN_PITCH * 4, (tb0 ? h1 : h0) + shx(tb0 ? h0 : h1, 1));
            if (!(lane & 29)) sts(so, st);
            bar_arrive(4, 352);
        }
    } else if (is_f2) {
        if (w < 14) {
            const bool live = w < 13 || lane < 16;
            const uint32_t* p = A + a_h1(side, w, (live ? lane : lane - 16) * 2);
            const uint32_t msk = live ? 0x7fff7fffu : 0u;
            uint32_t qo = sb + SM_PART2 + (g * 60 + w * 4 + tq) * 4; PIN(qo);
            mbar_wait(bars + 8 * (B_WO + 3));
            uint32_t af[8][4]; uint2 v;
            uint32_t stale = 1;
            poll1<false>(v, [&](uint2& u) { if (stale) u = ld_rlx2(p); }, [&](const uint2& u) { return stale = ((u.x ^ tag2) | (u.y ^ tag2)) & 0x80008000u; },
                         af, sb + SM_WO + w * 4096, bars + 8 * (B_WO + (w >> 1)), lane);
            float e[8][4];
            zero8(e);
            mma8(e, af, v.x & msk, v.y & msk);
            const float l0 = tb0 ? e[2][0] + e[3][1] : e[0][0] + e[1][1], h0 = tb0 ? e[2][2] + e[3][3] : e[0][2] + e[1][3];
            const float l1 = tb0 ? e[6][0] + e[7][1] : e[4][0] + e[5][1], h1 = tb0 ? e[6][2] + e[7][3] : e[4][2] + e[5][3];
            sts(qo, tb1 ? l1 : l0); sts(qo + 8 * 240, tb1 ? h1 : h0);
            bar_arrive(5, 480);
        }
    }
}

typedef CUresult (*EncodeFn)(CUtensorMap*, CUtensorMapDataType, cuuint32_t, void*, const cuuint64_t*, const cuuint64_t*,
                             const cuuint32_t*, const cuuint32_t*, CUtensorMapInterleave, CUtensorMapSwizzle,
                             CUtensorMapL2promotion, CUtensorMapFloatOOBfill);
float g_par[13] = {1000.f, 165.f, 164.f, 400.f, 164.f, 0.f, 250.f, 500.f, 500.f, 200.f, 100.f, 0.f, 0.f};

void make_map(EncodeFn enc, CUtensorMap* m, void* base, int cols, int rows, int bc, int br, CUtensorMapSwizzle sw = CU_TENSOR_MAP_SWIZZLE_64B) {
    cuuint64_t gd[2] = {(cuuint64_t)cols, (cuuint64_t)rows}; cuuint64_t gs[1] = {(cuuint64_t)cols * 2};
    cuuint32_t bd[2] = {(cuuint32_t)bc, (cuuint32_t)br}; cuuint32_t es[2] = {1, 1};
    enc(m, CU_TENSOR_MAP_DATA_TYPE_BFLOAT16, 2, base, gd, gs, bd, es, CU_TENSOR_MAP_INTERLEAVE_NONE, sw,
        CU_TENSOR_MAP_L2_PROMOTION_L2_128B, CU_TENSOR_MAP_FLOAT_OOB_FILL_NONE);
}

}

extern "C" void kernel_launch(void* const* d_in, const int* in_sizes, int n_in, void* d_out, int out_size) {
    (void)in_sizes; (void)n_in; (void)out_size;
    static EncodeFn enc = nullptr;
    static uint32_t* arena = nullptr;
    if (!enc) {
        void* sym = nullptr;
        cudaGetSymbolAddress(&sym, g_arena);
        arena = (uint32_t*)(((uintptr_t)sym + 524287) & ~(uintptr_t)524287);
        cudaDriverEntryPointQueryResult qr;
        cudaGetDriverEntryPoint("cuTensorMapEncodeTiled", (void**)&enc, cudaEnableDefault, &qr);
        cudaFuncSetAttribute(fused_decode_kernel, cudaFuncAttributeMaxDynamicSharedMemorySize, SM_TOTAL);
    }
    CUtensorMap mv, mwo, mw1, mw2;
    make_map(enc, &mv, d_in[2], DH, NH * SK, 32, 128);
    make_map(enc, &mwo, d_in[4], D, NH * DH, 32, 128);
    make_map(enc, &mw1, d_in[6], DFF, D, 32, 128);
    make_map(enc, &mw2, d_in[7], D, DFF, 16, 256, CU_TENSOR_MAP_SWIZZLE_32B);
    Params P = {(const __nv_bfloat16*)d_in[0], (const __nv_bfloat16*)d_in[1], (const __nv_bfloat16*)d_in[2], (const __nv_bfloat16*)d_in[3],
                (const __nv_bfloat16*)d_in[4], (const __nv_bfloat16*)d_in[6], (const __nv_bfloat16*)d_in[7], (__nv_bfloat16*)d_out, arena};
    float t = g_par[0];
    for (int i = 0; i < NSTEP; i++) {
        if (i == 16) t += g_par[12];
        if (i == 32) t += g_par[11];
        if (i == 40) t += g_par[3];
        if (i == 45) t += g_par[5];
        P.pf[i] = (uint32_t)t;
        P.ld[i] = (uint32_t)(t + g_par[i < 32 ? 7 : i < 40 ? 8 : i < 45 ? 9 : 10]);
        t += i < 32 ? g_par[1] : i < 40 ? 1.25f * g_par[2] : i < 45 ? 0.84375f * g_par[4] : 0.625f * g_par[6];
    }
    fused_decode_kernel<<<NCTA, NTHREADS, SM_TOTAL, cudaStreamPerThread>>>(P, mv, mwo, mw1, mw2);
}
```
